```python
import torch

def _softmax(x, axis=-1):
    return torch.softmax(x, dim=axis)
def _gelu(x):
    return torch.nn.functional.gelu(x, approximate="tanh")
def _silu(x):
    return torch.nn.functional.silu(x)
def _sigmoid(x):
    return torch.sigmoid(x)
def _layernorm(x, axis=-1, eps=1e-5):
    m = x.mean(dim=axis, keepdim=True)
    v = x.var(dim=axis, keepdim=True, unbiased=False)
    return (x - m) / torch.sqrt(v + eps)
def _scatter_add(tgt, idx, src, axis=0):
    return tgt.clone().index_add_(axis, idx, src)
def _segment_sum(src, seg, n):
    out = torch.zeros((n,) + src.shape[1:], dtype=src.dtype)
    return out.index_add_(0, seg, src)
def _pad(x, pw):
    flat = tuple(v for pair in reversed(pw) for v in pair)
    return torch.nn.functional.pad(x, flat)

kernel_name = 'gated_mix__softmax_full_mha__sliding_block__prompt'

def setup_inputs():

    _w = (lambda a: (lambda t: t.to(torch.bfloat16) if t.is_floating_point() else t)(torch.as_tensor(a)))
    def _A_setup():
        B, S, D = 1, 2048, 512
        return {
            "x": _w((lambda *s: torch.randn(*s, dtype=torch.bfloat16) * 0.05)(B, S, D)),
            "wqkv": _w((lambda *s: torch.randn(*s, dtype=torch.bfloat16) * 1.6)(D, 3 * D)),
            "wo": _w((lambda *s: torch.randn(*s, dtype=torch.bfloat16) * 0.1)(D, D)),
        }
    _A_in = _A_setup()

    def _B_setup():
        B, S, D = 1, 2048, 512
        return {
            "x": _w((lambda *s: torch.randn(*s, dtype=torch.bfloat16) * 0.05)(B, S, D)),
            "wqkv": _w((lambda *s: torch.randn(*s, dtype=torch.bfloat16) * 1.6)(D, 3 * D)),
            "wo": _w((lambda *s: torch.randn(*s, dtype=torch.bfloat16) * 0.05)(D, D)),
        }
    _B_in = _B_setup()

    return {
        "A_x": _A_in["x"],
        "A_wqkv": _A_in["wqkv"],
        "A_wo": _A_in["wo"],
        "B_x": _B_in["x"],
        "B_wqkv": _B_in["wqkv"],
        "B_wo": _B_in["wo"],
        "gate_w": _w((lambda *s: torch.randn(*s, dtype=torch.bfloat16) * 0.05)(512) * 16.0),
    }

def reference(A_x, A_wqkv, A_wo, B_x, B_wqkv, B_wo, gate_w):
    def _A_ref(x, wqkv, wo):
        B, S, D = x.shape
        H = 32; Dh = D // H
        qkv = (lambda x, *d: x.permute(*d))((x @ wqkv).reshape(B, S, 3, H, Dh), 2, 0, 3, 1, 4)
        q, k, v = qkv[0], qkv[1], qkv[2]
        scale = Dh ** -0.5
        scores = torch.einsum("bhqd,bhkd->bhqk", q, k) * scale
        p = _softmax(scores, axis=-1)
        o = torch.einsum("bhqk,bhkd->bhqd", p, v)
        return (lambda x, *d: x.permute(*d))(o, 0, 2, 1, 3).reshape(B, S, D) @ wo

    def _B_ref(x, wqkv, wo):
        B, S, D = x.shape
        H = 32; Dh = D // H; W = 256
        qkv = (lambda x, *d: x.permute(*d))((x @ wqkv).reshape(B, S, 3, H, Dh), 2, 0, 3, 1, 4)
        q, k, v = qkv[0], qkv[1], qkv[2]
        scores = torch.einsum("bhqd,bhkd->bhqk", q, k) * (Dh ** -0.5)
        idx = torch.arange(S)
        mask = (idx[:, None] - idx[None, :] >= 0) & (idx[:, None] - idx[None, :] < W)
        scores = torch.where(mask[None, None], scores, -1e9)
        p = _softmax(scores, axis=-1)
        o = torch.einsum("bhqk,bhkd->bhqd", p, v)
        return (lambda x, *d: x.permute(*d))(o, 0, 2, 1, 3).reshape(B, S, D) @ wo

    x = A_x
    g = _sigmoid((x * gate_w).sum(-1, keepdims=True))
    a = _A_ref(x, A_wqkv, A_wo)
    b = _B_ref(x, B_wqkv, B_wo)
    return g * a + (1 - g) * b
```

```cpp
#include <cuda_runtime.h>
#include <cuda_bf16.h>
#include <cuda.h>
#include <stdint.h>

namespace {

constexpr int SEQ = 2048, DM = 512;

__device__ __align__(1024) uint8_t g_kv[128 * 61440];
__device__ unsigned long long g_flag[128];
__device__ uint4 g_qsave[128 * 7 * 512];
__device__ float g_gate[SEQ];
__device__ __align__(1024) __nv_bfloat16 g_ocat[SEQ * 1024];

#define STAMP(i)
#define STAMPH(i)
#define STAMPK(i)
#define STAMPKW()
#define STAMP2(i)

__device__ __forceinline__ uint32_t smem_u32(const void* p) { return (uint32_t)__cvta_generic_to_shared(p); }
__device__ __forceinline__ void wg_fence() { asm volatile("wgmma.fence.sync.aligned;" ::: "memory"); }
__device__ __forceinline__ void wg_commit() { asm volatile("wgmma.commit_group.sync.aligned;" ::: "memory"); }
template <int N> __device__ __forceinline__ void wg_wait() { asm volatile("wgmma.wait_group.sync.aligned %0;" ::"n"(N) : "memory"); }
constexpr uint32_t SMEM_BASE = 1024;
__host__ __device__ constexpr uint64_t make_desc(uint32_t addr, uint32_t lbo, uint32_t sbo, uint32_t mode) {
    return (uint64_t)((addr & 0x3FFFF) >> 4) | ((uint64_t)(lbo >> 4) << 16) | ((uint64_t)(sbo >> 4) << 32) | ((uint64_t)mode << 62);
}
template <int N> __device__ __forceinline__ void fence_regs(float (&r)[N]) {
#pragma unroll
    for (int i = 0; i < N; i++) asm volatile("" : "+f"(r[i])::"memory");
}
template <int N> __device__ __forceinline__ void fence_regs(uint32_t (&r)[N]) {
#pragma unroll
    for (int i = 0; i < N; i++) asm volatile("" : "+r"(r[i])::"memory");
}
__device__ __forceinline__ void mbar_init(uint32_t bar, uint32_t count) {
    asm volatile("mbarrier.init.shared::cta.b64 [%0], %1;" ::"r"(bar), "r"(count) : "memory");
}
__device__ __forceinline__ void mbar_expect_tx(uint32_t bar, uint32_t bytes) {
    asm volatile("mbarrier.arrive.expect_tx.shared::cta.b64 _, [%0], %1;" ::"r"(bar), "r"(bytes) : "memory");
}
__device__ __forceinline__ void mbar_arrive_cluster(uint32_t bar, uint32_t cta) {
    asm volatile("{\n.reg .b32 ra;\nmapa.shared::cluster.u32 ra, %0, %1;\n"
                 "mbarrier.arrive.shared::cluster.b64 _, [ra];\n}\n" ::"r"(bar), "r"(cta) : "memory");
}
__device__ __forceinline__ bool mbar_try(uint32_t bar, uint32_t parity) {
    uint32_t ok;
    asm volatile("{\n.reg .pred p;\nmbarrier.try_wait.parity.shared::cta.b64 p, [%1], %2;\nselp.u32 %0, 1, 0, p;\n}\n"
                 : "=r"(ok) : "r"(bar), "r"(parity) : "memory");
    return ok != 0;
}
__device__ __forceinline__ void mbar_wait(uint32_t bar, uint32_t parity) {
    if (mbar_try(bar, parity)) return;
#pragma unroll 1
    for (uint32_t i = 0; i < (1u << 22); i++)
        if (mbar_try(bar, parity)) return;
    __trap();
}
__device__ __forceinline__ void cluster_sync() {
    asm volatile("barrier.cluster.arrive.relaxed.aligned;\nbarrier.cluster.wait.aligned;" ::: "memory");
}
template <int ID, int N> __device__ __forceinline__ void named_sync() { asm volatile("bar.sync %0, %1;" ::"n"(ID), "n"(N) : "memory"); }
__device__ __forceinline__ void fence_async_smem() { asm volatile("fence.proxy.async.shared::cta;" ::: "memory"); }
__device__ __forceinline__ void tma_2d(uint32_t dst, const CUtensorMap* tm, int c0, int c1, uint32_t bar) {
    asm volatile("cp.async.bulk.tensor.2d.shared::cluster.global.mbarrier::complete_tx::bytes [%0], [%1, {%3, %4}], [%2];"
                 ::"r"(dst), "l"(tm), "r"(bar), "r"(c0), "r"(c1) : "memory");
}
__device__ __forceinline__ void tma_2d_mc(uint32_t dst, const CUtensorMap* tm, int c0, int c1, uint32_t bar, uint16_t mask) {
    asm volatile("cp.async.bulk.tensor.2d.shared::cluster.global.mbarrier::complete_tx::bytes.multicast::cluster [%0], [%1, {%3, %4}], [%2], %5;"
                 ::"r"(dst), "l"(tm), "r"(bar), "r"(c0), "r"(c1), "h"(mask) : "memory");
}
__device__ __forceinline__ void tma_4d(uint32_t dst, const CUtensorMap* tm, int c0, int c1, int c2, int c3, uint32_t bar) {
    asm volatile("cp.async.bulk.tensor.4d.shared::cluster.global.mbarrier::complete_tx::bytes [%0], [%1, {%3, %4, %5, %6}], [%2];"
                 ::"r"(dst), "l"(tm), "r"(bar), "r"(c0), "r"(c1), "r"(c2), "r"(c3) : "memory");
}
__device__ __forceinline__ void bulk_g2s(uint32_t dst, const void* src, uint32_t bytes, uint32_t bar) {
    asm volatile("cp.async.bulk.shared::cluster.global.mbarrier::complete_tx::bytes [%0], [%1], %2, [%3];"
                 ::"r"(dst), "l"(src), "r"(bytes), "r"(bar) : "memory");
}
__device__ __forceinline__ void bulk_s2g(void* dst, uint32_t src, uint32_t bytes) {
    asm volatile("cp.async.bulk.global.shared::cta.bulk_group [%0], [%1], %2;" ::"l"(dst), "r"(src), "r"(bytes) : "memory");
}
__device__ __forceinline__ void stmatrix_x4(uint32_t addr, uint32_t r0, uint32_t r1, uint32_t r2, uint32_t r3) {
    asm volatile("stmatrix.sync.aligned.m8n8.x4.shared.b16 [%0], {%1, %2, %3, %4};" ::"r"(addr), "r"(r0), "r"(r1), "r"(r2), "r"(r3) : "memory");
}
__device__ __forceinline__ float ex2(float x) { float y; asm("ex2.approx.ftz.f32 %0, %1;" : "=f"(y) : "f"(x)); return y; }
__device__ __forceinline__ uint32_t pack_bf16(float lo, float hi) {
    uint32_t r; asm("cvt.rn.bf16x2.f32 %0, %1, %2;" : "=r"(r) : "f"(hi), "f"(lo)); return r;
}

__device__ __forceinline__ void wgmma_ss_n96_tb(float (&d)[48], uint64_t da, uint64_t db) {
    asm volatile("wgmma.mma_async.sync.aligned.m64n96k16.f32.bf16.bf16 {"
        "%0, %1, %2, %3, %4, %5, %6, %7, %8, %9, %10, %11, %12, %13, %14, %15 "
        "%16, %17, %18, %19, %20, %21, %22, %23, %24, %25, %26, %27, %28, %29, %30, %31 "
        "%32, %33, %34, %35, %36, %37, %38, %39, %40, %41, %42, %43, %44, %45, %46, %47}, "
        "%48, %49, 1, 1, 1, 0, 1;\n"
        : "+f"(d[0]), "+f"(d[1]), "+f"(d[2]), "+f"(d[3]), "+f"(d[4]), "+f"(d[5]), "+f"(d[6]), "+f"(d[7]),
          "+f"(d[8]), "+f"(d[9]), "+f"(d[10]), "+f"(d[11]), "+f"(d[12]), "+f"(d[13]), "+f"(d[14]), "+f"(d[15]),
          "+f"(d[16]), "+f"(d[17]), "+f"(d[18]), "+f"(d[19]), "+f"(d[20]), "+f"(d[21]), "+f"(d[22]), "+f"(d[23]),
          "+f"(d[24]), "+f"(d[25]), "+f"(d[26]), "+f"(d[27]), "+f"(d[28]), "+f"(d[29]), "+f"(d[30]), "+f"(d[31]),
          "+f"(d[32]), "+f"(d[33]), "+f"(d[34]), "+f"(d[35]), "+f"(d[36]), "+f"(d[37]), "+f"(d[38]), "+f"(d[39]),
          "+f"(d[40]), "+f"(d[41]), "+f"(d[42]), "+f"(d[43]), "+f"(d[44]), "+f"(d[45]), "+f"(d[46]), "+f"(d[47])
        : "l"(da), "l"(db));
}
__device__ __forceinline__ void wgmma_ss_n64_tb(float (&d)[32], uint64_t da, uint64_t db) {
    asm volatile("wgmma.mma_async.sync.aligned.m64n64k16.f32.bf16.bf16 {"
        "%0, %1, %2, %3, %4, %5, %6, %7, %8, %9, %10, %11, %12, %13, %14, %15 "
        "%16, %17, %18, %19, %20, %21, %22, %23, %24, %25, %26, %27, %28, %29, %30, %31}, "
        "%32, %33, 1, 1, 1, 0, 1;\n"
        : "+f"(d[0]), "+f"(d[1]), "+f"(d[2]), "+f"(d[3]), "+f"(d[4]), "+f"(d[5]), "+f"(d[6]), "+f"(d[7]),
          "+f"(d[8]), "+f"(d[9]), "+f"(d[10]), "+f"(d[11]), "+f"(d[12]), "+f"(d[13]), "+f"(d[14]), "+f"(d[15]),
          "+f"(d[16]), "+f"(d[17]), "+f"(d[18]), "+f"(d[19]), "+f"(d[20]), "+f"(d[21]), "+f"(d[22]), "+f"(d[23]),
          "+f"(d[24]), "+f"(d[25]), "+f"(d[26]), "+f"(d[27]), "+f"(d[28]), "+f"(d[29]), "+f"(d[30]), "+f"(d[31])
        : "l"(da), "l"(db));
}
template <uint32_t HI>
__device__ __forceinline__ void wgmma_rs_n64_zero(float (&d)[32], uint32_t a0, uint32_t a1, uint32_t a2, uint32_t a3, uint32_t db_lo) {
    asm volatile("{\n.reg .b64 dsc;\nmov.b64 dsc, {%36, %37};\n"
        "wgmma.mma_async.sync.aligned.m64n64k16.f32.bf16.bf16 {"
        "%0, %1, %2, %3, %4, %5, %6, %7, %8, %9, %10, %11, %12, %13, %14, %15 "
        "%16, %17, %18, %19, %20, %21, %22, %23, %24, %25, %26, %27, %28, %29, %30, %31}, "
        "{%32, %33, %34, %35}, dsc, 0, 1, 1, 0;\n}\n"
        : "+f"(d[0]), "+f"(d[1]), "+f"(d[2]), "+f"(d[3]), "+f"(d[4]), "+f"(d[5]), "+f"(d[6]), "+f"(d[7]),
          "+f"(d[8]), "+f"(d[9]), "+f"(d[10]), "+f"(d[11]), "+f"(d[12]), "+f"(d[13]), "+f"(d[14]), "+f"(d[15]),
          "+f"(d[16]), "+f"(d[17]), "+f"(d[18]), "+f"(d[19]), "+f"(d[20]), "+f"(d[21]), "+f"(d[22]), "+f"(d[23]),
          "+f"(d[24]), "+f"(d[25]), "+f"(d[26]), "+f"(d[27]), "+f"(d[28]), "+f"(d[29]), "+f"(d[30]), "+f"(d[31])
        : "r"(a0), "r"(a1), "r"(a2), "r"(a3), "r"(db_lo), "n"(HI));
}
__device__ __forceinline__ void wgmma_rs_n24_tb64(float (&d)[12], uint32_t a0, uint32_t a1, uint32_t a2, uint32_t a3, uint64_t db) {
    asm volatile("wgmma.mma_async.sync.aligned.m64n24k16.f32.bf16.bf16 {"
        "%0, %1, %2, %3, %4, %5, %6, %7, %8, %9, %10, %11}, "
        "{%12, %13, %14, %15}, %16, 1, 1, 1, 1;\n"
        : "+f"(d[0]), "+f"(d[1]), "+f"(d[2]), "+f"(d[3]), "+f"(d[4]), "+f"(d[5]), "+f"(d[6]), "+f"(d[7]),
          "+f"(d[8]), "+f"(d[9]), "+f"(d[10]), "+f"(d[11])
        : "r"(a0), "r"(a1), "r"(a2), "r"(a3), "l"(db));
}
__device__ __forceinline__ void wgmma_rs_n16_zero64(float (&d)[8], uint32_t a0, uint32_t a1, uint32_t a2, uint32_t a3, uint64_t db) {
    asm volatile("wgmma.mma_async.sync.aligned.m64n16k16.f32.bf16.bf16 {"
        "%0, %1, %2, %3, %4, %5, %6, %7}, "
        "{%8, %9, %10, %11}, %12, 0, 1, 1, 0;\n"
        : "+f"(d[0]), "+f"(d[1]), "+f"(d[2]), "+f"(d[3]), "+f"(d[4]), "+f"(d[5]), "+f"(d[6]), "+f"(d[7])
        : "r"(a0), "r"(a1), "r"(a2), "r"(a3), "l"(db));
}
__device__ __forceinline__ void wgmma_rs_n48_64(float (&d)[24], uint32_t a0, uint32_t a1, uint32_t a2, uint32_t a3, uint64_t db) {
    asm volatile("wgmma.mma_async.sync.aligned.m64n48k16.f32.bf16.bf16 {"
        "%0, %1, %2, %3, %4, %5, %6, %7, %8, %9, %10, %11, %12, %13, %14, %15 "
        "%16, %17, %18, %19, %20, %21, %22, %23}, "
        "{%24, %25, %26, %27}, %28, 1, 1, 1, 0;\n"
        : "+f"(d[0]), "+f"(d[1]), "+f"(d[2]), "+f"(d[3]), "+f"(d[4]), "+f"(d[5]), "+f"(d[6]), "+f"(d[7]),
          "+f"(d[8]), "+f"(d[9]), "+f"(d[10]), "+f"(d[11]), "+f"(d[12]), "+f"(d[13]), "+f"(d[14]), "+f"(d[15]),
          "+f"(d[16]), "+f"(d[17]), "+f"(d[18]), "+f"(d[19]), "+f"(d[20]), "+f"(d[21]), "+f"(d[22]), "+f"(d[23])
        : "r"(a0), "r"(a1), "r"(a2), "r"(a3), "l"(db));
}
template <uint32_t HI>
__device__ __forceinline__ void wgmma_rs_n24_tb(float (&d)[12], uint32_t a0, uint32_t a1, uint32_t a2, uint32_t a3, uint32_t db_lo) {
    asm volatile("{\n.reg .b64 dsc;\nmov.b64 dsc, {%16, %17};\n"
        "wgmma.mma_async.sync.aligned.m64n24k16.f32.bf16.bf16 {"
        "%0, %1, %2, %3, %4, %5, %6, %7, %8, %9, %10, %11}, "
        "{%12, %13, %14, %15}, dsc, 1, 1, 1, 1;\n}\n"
        : "+f"(d[0]), "+f"(d[1]), "+f"(d[2]), "+f"(d[3]), "+f"(d[4]), "+f"(d[5]), "+f"(d[6]), "+f"(d[7]),
          "+f"(d[8]), "+f"(d[9]), "+f"(d[10]), "+f"(d[11])
        : "r"(a0), "r"(a1), "r"(a2), "r"(a3), "r"(db_lo), "n"(HI));
}

constexpr int NSLOT = 5, NSTEP = 16;
constexpr uint32_t XS_BYTES = 32768, WS_BYTES = 12288, WBUF = NSLOT * XS_BYTES;
constexpr uint32_t REC = 5120, RECD = REC / 16, KVA = 0, KVB = 32 * REC, BARS = KVB + 12 * REC;
constexpr uint32_t FULL_BAR = BARS, EMPTY_BAR = BARS + 40, X_BAR = BARS + 80, REDO = BARS + 96, STATS = BARS + 128,
                   CONSTS = BARS + 192;
constexpr uint32_t SMEM1_BYTES = BARS + 320;
static_assert(WBUF + 3 * WS_BYTES <= BARS, "ring too large");

constexpr uint32_t KHI = (uint32_t)(make_desc(0, 1024, 128, 0) >> 32), VHI = (uint32_t)(make_desc(0, 128, 1024, 0) >> 32);
constexpr uint32_t dKA = (uint32_t)make_desc(SMEM_BASE + KVA, 1024, 128, 0), dVA = (uint32_t)make_desc(SMEM_BASE + KVA + 2048, 128, 1024, 0);
constexpr uint32_t dKB = (uint32_t)make_desc(SMEM_BASE + KVB, 1024, 128, 0), dVB = (uint32_t)make_desc(SMEM_BASE + KVB + 2048, 128, 1024, 0);

constexpr float QSCALE = 0.25f * 1.4426950408889634f;
#define XMASK 0x0
#define QKORD 0
constexpr float EXP_MAGIC = 381.401059f;

__device__ __forceinline__ uint32_t exp2_sw(float y0, float y1, uint32_t one2) {
    const uint32_t w = __byte_perm(__float_as_uint(y0), __float_as_uint(y1), 0x6521);
    uint32_t u, z;
    asm("lop3.b32 %0, %1, 0x007f007f, %2, 0xEA;" : "=r"(u) : "r"(w), "r"(one2));
    asm("fma.rn.bf16x2 %0, %1, %1, %2;" : "=r"(z) : "r"(u), "r"(0x40034003u));
    return w - u + z;
}

__device__ __forceinline__ void make_masks(uint32_t (&M)[9]) {
    uint32_t t;
    asm volatile("mov.u32 %0, %tid.x;" : "=r"(t));
    const int dbase = (int)((t >> 1) & 48) + (int)((t >> 2) & 7) - 2 * (int)(t & 3);
#pragma unroll
    for (int i = 0; i < 9; i++) { const int d = dbase + 8 * (i - 7); M[i] = d >= 1 ? 0xffffffffu : (d == 0 ? 0x0000ffffu : 0u); }
}

struct Scores { float m[8], p[24]; };

__device__ __forceinline__ void load_magic(Scores& S, int i, uint32_t caddr) {
    asm volatile("ld.volatile.shared.v4.f32 {%0, %1, %2, %3}, [%4];"
                 : "=f"(S.p[4 * i]), "=f"(S.p[4 * i + 1]), "=f"(S.p[4 * i + 2]), "=f"(S.p[4 * i + 3]) : "r"(caddr + 16 * i));
}
__device__ __forceinline__ void issue_qk(Scores& S, const uint32_t (&q)[4], uint32_t kd) {
    uint64_t kd64;
    asm("mov.b64 %0, {%1, %2};" : "=l"(kd64) : "r"(kd), "n"(KHI));
    wgmma_rs_n16_zero64(S.m, q[0], q[1], q[2], q[3], kd64);
    wgmma_rs_n48_64(S.p, q[0], q[1], q[2], q[3], kd64 + 16);
}

template <int MODE, bool QK>
__device__ __forceinline__ void attn_step(Scores& S, float (&O)[12], const uint32_t (&qn)[4], uint32_t kd_next, uint32_t vd,
                                          uint32_t one2, uint32_t caddr) {
    uint32_t P[16], M[9];
    if (MODE) make_masks(M);
#pragma unroll
    for (int i = 0; i < 6; i++) {
        if (i < 2) P[2 * i] = pack_bf16(ex2(S.m[4 * i]), ex2(S.m[4 * i + 1]));
#pragma unroll
        for (int h = 0; h < 2; h++) {
            const float y0 = S.p[4 * i + 2 * h], y1 = S.p[4 * i + 2 * h + 1];
            P[4 + 2 * i + h] = ((XMASK >> (2 * i + h)) & 1) ? pack_bf16(ex2(y0), ex2(y1)) : exp2_sw(y0, y1, one2);
        }
        if (QK) load_magic(S, i, caddr);
        if (i < 2) P[2 * i + 1] = pack_bf16(ex2(S.m[4 * i + 2]), ex2(S.m[4 * i + 3]));
    }
#pragma unroll
    for (int i = 0; i < 16; i++) {
        if (MODE == 1) P[i] &= M[(i & 1) - (i >> 1) + 7];
        if (MODE == 2) P[i] &= ~M[(i & 1) - (i >> 1) + 7];
    }
    uint64_t vd64;
    asm("mov.b64 %0, {%1, %2};" : "=l"(vd64) : "r"(vd), "n"(VHI));
    fence_regs(P); fence_regs(S.p);
    wg_fence();
    if (QK && QKORD == 0) issue_qk(S, qn, kd_next);
#pragma unroll
    for (int k = 0; k < 4; k++) wgmma_rs_n24_tb64(O, P[4 * k], P[4 * k + 1], P[4 * k + 2], P[4 * k + 3], vd64 + k * 16);
    if (QK && QKORD == 2) issue_qk(S, qn, kd_next);
    wg_commit();
    wg_wait<0>();
    fence_regs(S.m); fence_regs(S.p); fence_regs(P); fence_regs(O);
}

template <int UNR>
__device__ __forceinline__ void attn_run(Scores& S, float (&O)[12], const uint32_t (&q)[4], uint32_t vd, int n, uint32_t one2, uint32_t caddr) {
#pragma unroll 1
    for (const uint32_t vend = vd + n * RECD; vd != vend; vd += UNR * RECD) {
#pragma unroll
        for (int u = 0; u < UNR; u++) attn_step<0, true>(S, O, q, vd + (u + 1) * RECD + (dKA - dVA), vd + u * RECD, one2, caddr);
    }
}
__device__ __forceinline__ void zero_o(float (&O)[12]) {
#pragma unroll
    for (int i = 0; i < 12; i++) O[i] = 0.f;
    fence_regs(O);
}

__device__ __forceinline__ void attn_slow(float (&O)[12], const uint32_t (&q)[4], uint32_t kd, uint32_t vd,
                                          int ntiles, bool mask_first, bool mask_last) {
    const int lane = threadIdx.x & 31;
    const int dbase = ((threadIdx.x >> 5) & 3) * 16 + (lane >> 2) - 2 * (lane & 3);
    uint32_t P[16];
    float S[32];
    float m0 = -INFINITY, m1 = -INFINITY;
#pragma unroll
    for (int i = 0; i < 32; i++) S[i] = 0.f;
#pragma unroll
    for (int i = 0; i < 12; i++) O[i] = 0.f;
#pragma unroll 1
    for (int j = 0; j < ntiles; j++) {
        fence_regs(S);
        wg_fence();
        wgmma_rs_n64_zero<KHI>(S, q[0], q[1], q[2], q[3], kd + j * RECD);
        wg_commit();
        wg_wait<0>();
        fence_regs(S);
        const bool mf = mask_first && j == 0, ml = mask_last && j == ntiles - 1;
        if (mf || ml) {
#pragma unroll
            for (int i = 0; i < 32; i++) {
                const int d = dbase + 8 * ((i >> 1) & 1) - 8 * (i >> 2) - (i & 1);
                const bool keep = ml ? (d >= 0) : (d < 0);
                if (!keep) S[i] = -1e9f * 1.4426950408889634f;
            }
        }
        float x0 = m0, x1 = m1;
#pragma unroll
        for (int b = 0; b < 8; b++) {
            x0 = fmaxf(x0, fmaxf(S[4 * b], S[4 * b + 1]));
            x1 = fmaxf(x1, fmaxf(S[4 * b + 2], S[4 * b + 3]));
        }
        x0 = fmaxf(x0, __shfl_xor_sync(~0u, x0, 1)); x0 = fmaxf(x0, __shfl_xor_sync(~0u, x0, 2));
        x1 = fmaxf(x1, __shfl_xor_sync(~0u, x1, 1)); x1 = fmaxf(x1, __shfl_xor_sync(~0u, x1, 2));
        const float a0 = ex2(m0 - x0), a1 = ex2(m1 - x1);
        m0 = x0; m1 = x1;
#pragma unroll
        for (int b = 0; b < 3; b++) { O[4 * b] *= a0; O[4 * b + 1] *= a0; O[4 * b + 2] *= a1; O[4 * b + 3] *= a1; }
#pragma unroll
        for (int b = 0; b < 8; b++) {
            P[2 * b] = pack_bf16(ex2(S[4 * b] - m0), ex2(S[4 * b + 1] - m0));
            P[2 * b + 1] = pack_bf16(ex2(S[4 * b + 2] - m1), ex2(S[4 * b + 3] - m1));
        }
        fence_regs(P); fence_regs(O);
        wg_fence();
#pragma unroll
        for (int k = 0; k < 4; k++) wgmma_rs_n24_tb<VHI>(O, P[4 * k], P[4 * k + 1], P[4 * k + 2], P[4 * k + 3], vd + j * RECD + k * 16);
        wg_commit();
        wg_wait<0>();
        fence_regs(P); fence_regs(O);
    }
}

__device__ __forceinline__ bool shift_free_ok(float q2, float k2, bool extra = true) {
    return __all_sync(~0u, extra && q2 * k2 <= 107.f * 107.f);
}

__device__ __forceinline__ bool store_o(const float (&O)[12], __nv_bfloat16* dst  ) {
    float i0, i1;
    asm("rcp.approx.ftz.f32 %0, %1;" : "=f"(i0) : "f"(O[8]));
    asm("rcp.approx.ftz.f32 %0, %1;" : "=f"(i1) : "f"(O[10]));
    *reinterpret_cast<uint32_t*>(dst) = pack_bf16(O[0] * i0, O[1] * i0);
    *reinterpret_cast<uint32_t*>(dst + 8) = pack_bf16(O[4] * i0, O[5] * i0);
    *reinterpret_cast<uint32_t*>(dst + 8 * 1024) = pack_bf16(O[2] * i1, O[3] * i1);
    *reinterpret_cast<uint32_t*>(dst + 8 * 1024 + 8) = pack_bf16(O[6] * i1, O[7] * i1);
    const float s0 = (fabsf(O[0]) + fabsf(O[1])) + (fabsf(O[4]) + fabsf(O[5]));
    const float s1 = (fabsf(O[2]) + fabsf(O[3])) + (fabsf(O[6]) + fabsf(O[7]));
    return s0 >= 0x1p-96f && s1 >= 0x1p-96f && s0 <= 0x1p126f && s1 <= 0x1p126f;
}

__device__ __forceinline__ void row_norm_stats(const float (&a)[48], const float (&b)[48], int lane, uint32_t stats_addr) {
    float s[4][4], t[4][2];
    const bool o1 = lane & 1, o2 = lane & 2;
#pragma unroll
    for (int i = 0; i < 4; i++) {
        const float* p = a + 24 * (i >> 1) + 8 * (i & 1);
        const float* r = b + 24 * (i >> 1) + 8 * (i & 1);
        s[i][0] = (p[0] * p[0] + p[1] * p[1]) + (p[4] * p[4] + p[5] * p[5]);
        s[i][1] = (p[2] * p[2] + p[3] * p[3]) + (p[6] * p[6] + p[7] * p[7]);
        s[i][2] = (r[0] * r[0] + r[1] * r[1]) + (r[4] * r[4] + r[5] * r[5]);
        s[i][3] = (r[2] * r[2] + r[3] * r[3]) + (r[6] * r[6] + r[7] * r[7]);
    }
#pragma unroll
    for (int i = 0; i < 4; i++) {
        t[i][0] = (o1 ? s[i][1] : s[i][0]) + __shfl_xor_sync(~0u, o1 ? s[i][0] : s[i][1], 1);
        t[i][1] = (o1 ? s[i][3] : s[i][2]) + __shfl_xor_sync(~0u, o1 ? s[i][2] : s[i][3], 1);
    }
    uint32_t m[4];
#pragma unroll
    for (int i = 0; i < 4; i++) {
        const float v = (o2 ? t[i][1] : t[i][0]) + __shfl_xor_sync(~0u, o2 ? t[i][0] : t[i][1], 2);
        m[i] = __float_as_uint(v);
    }
#pragma unroll
    for (int i = 0; i < 4; i++) m[i] = __reduce_max_sync(~0u, m[i]);
    const uint32_t mv = o2 ? (o1 ? m[3] : m[2]) : (o1 ? m[1] : m[0]);
    if (lane < 4) asm volatile("red.shared.max.u32 [%0], %1;" ::"r"(stats_addr + 4 * lane), "r"(mv) : "memory");
}

__global__ void __launch_bounds__(512, 1)
qkv_attn_kernel(const __grid_constant__ CUtensorMap tm_x, const __grid_constant__ CUtensorMap tm_wa,
                const __grid_constant__ CUtensorMap tm_wb, const __nv_bfloat16* __restrict__ x,
                const __nv_bfloat16* __restrict__ gate_w) {
    extern __shared__ __align__(1024) uint8_t sp[];
    const uint32_t sb = smem_u32(sp);
    if ((sb & 0x3FFFF) != SMEM_BASE) __trap();
    const int tid = threadIdx.x, lane = tid & 31;
    const int warp = __shfl_sync(~0u, tid >> 5, 0), wg = warp >> 2, w4 = warp & 3;
    const int bid = blockIdx.x, rank = bid & 1, qb = (bid >> 1) & 3, head = ((bid >> 3) << 1) | rank;
    const int slot = head * 4 + qb;
    STAMP(0);
    const int grow = qb * 512 + head * 16 + warp;
    uint4 gx[2], gw[2];
#pragma unroll
    for (int c = 0; c < 2; c++) {
        gx[c] = __ldg(reinterpret_cast<const uint4*>(x + (size_t)grow * DM) + lane + 32 * c);
        gw[c] = __ldg(reinterpret_cast<const uint4*>(gate_w) + lane + 32 * c);
    }

    if (tid == 0) {
        asm volatile("prefetch.tensormap [%0];" ::"l"(&tm_x) : "memory");
        asm volatile("prefetch.tensormap [%0];" ::"l"(&tm_wa) : "memory");
        asm volatile("prefetch.tensormap [%0];" ::"l"(&tm_wb) : "memory");
        for (int s = 0; s < NSLOT; s++) { mbar_init(sb + FULL_BAR + 8 * s, 1); mbar_init(sb + EMPTY_BAR + 8 * s, 8); }
        mbar_init(sb + X_BAR, 3);
        asm volatile("fence.mbarrier_init.release.cluster;" ::: "memory");
        mbar_expect_tx(sb + FULL_BAR, XS_BYTES + WS_BYTES);
        tma_2d(sb, &tm_x, 0, qb * 512, sb + FULL_BAR);
        tma_4d(sb + WBUF, &tm_wa, 0, 0, head, 0, sb + FULL_BAR);
        tma_4d(sb + WBUF + 6144, &tm_wb, 0, 0, head, 0, sb + FULL_BAR);
        mbar_expect_tx(sb + FULL_BAR + 8, XS_BYTES);
        tma_2d(sb + XS_BYTES, &tm_x, 0, qb * 512 + 256, sb + FULL_BAR + 8);
        for (int t = 2; t < NSLOT; t++) {
            mbar_expect_tx(sb + FULL_BAR + 8 * t, (t & 1) ? XS_BYTES : XS_BYTES + WS_BYTES);
            if (!(t & 1)) {
                tma_4d(sb + WBUF + (t >> 1) * WS_BYTES, &tm_wa, 0, (t >> 1) * 64, head, 0, sb + FULL_BAR + 8 * t);
                tma_4d(sb + WBUF + (t >> 1) * WS_BYTES + 6144, &tm_wb, 0, (t >> 1) * 64, head, 0, sb + FULL_BAR + 8 * t);
            }
        }
    }
    if (tid >= 32 && tid < 44) reinterpret_cast<uint32_t*>(sp + REDO)[tid - 32] = tid == 36 ? 0xbf80bf80u : 0u;
    if (tid >= 64 && tid < 88) reinterpret_cast<float*>(sp + CONSTS)[tid - 64] = ((XMASK >> ((tid - 64) >> 1)) & 1) ? 0.f : EXP_MAGIC;
    __syncwarp();
    cluster_sync();
    if (tid == 0) {
        for (int t = 2 + rank; t < NSLOT; t += 2)
            tma_2d_mc(sb + t * XS_BYTES, &tm_x, (t >> 1) * 64, qb * 512 + rank * 256, sb + FULL_BAR + 8 * t, 3);
    }
    __syncwarp();
    {
        float ga = 0.f, gb = 0.f;
#pragma unroll
        for (int c = 0; c < 2; c++) {
            const uint32_t av[4] = {gx[c].x, gx[c].y, gx[c].z, gx[c].w}, gv[4] = {gw[c].x, gw[c].y, gw[c].z, gw[c].w};
#pragma unroll
            for (int i = 0; i < 4; i++) {
                ga += __uint_as_float(av[i] << 16) * __uint_as_float(gv[i] << 16);
                gb += __uint_as_float(av[i] & 0xffff0000u) * __uint_as_float(gv[i] & 0xffff0000u);
            }
        }
        ga += gb;
#pragma unroll
        for (int o = 16; o; o >>= 1) ga += __shfl_xor_sync(~0u, ga, o);
        if (lane == 0) g_gate[grow] = __fdividef(1.f, 1.f + __expf(-ga));
    }

    uint32_t qa0[4], qa1[4], qb0[4], qb1[4];
    uint4* const qs = g_qsave + bid * 3584 + tid;
    {
        float acc0[48], acc1[48];
#pragma unroll
        for (int i = 0; i < 48; i++) { acc0[i] = 0.f; acc1[i] = 0.f; }
        fence_regs(acc0); fence_regs(acc1);
        const uint64_t da0 = make_desc(SMEM_BASE + wg * 8192, 16, 1024, 1);
        const uint64_t db0 = make_desc(SMEM_BASE + WBUF, 2048, 256, 3);
#pragma unroll
        for (int t = 0; t < NSTEP; t++) {
            const int s = t % NSLOT;
            mbar_wait(sb + FULL_BAR + 8 * s, (t / NSLOT) & 1);
            const uint64_t da = da0 + (uint64_t)(s * (XS_BYTES >> 4)), db = db0 + (uint64_t)(((t >> 1) % 3) * (WS_BYTES >> 4));
            wg_fence();
#pragma unroll
            for (int k = 0; k < 4; k++) {
                if (t & 1) wgmma_ss_n96_tb(acc1, da + 2 * k, db + 32 * k);
                else wgmma_ss_n96_tb(acc0, da + 2 * k, db + 32 * k);
            }
            wg_commit();
            if (t >= 1 && t - 1 + NSLOT < NSTEP) {
                wg_wait<1>();
                const int ps = (t - 1) % NSLOT, nt = t - 1 + NSLOT;
                if (w4 >= 2 && lane == 0) mbar_arrive_cluster(sb + EMPTY_BAR + 8 * ps, w4 & 1);
                if (tid == 0) {
                    mbar_expect_tx(sb + FULL_BAR + 8 * ps, (nt & 1) ? XS_BYTES : XS_BYTES + WS_BYTES);
                    if (!(nt & 1) || rank == 1) mbar_wait(sb + EMPTY_BAR + 8 * ps, ((t - 1) / NSLOT) & 1);
                    if ((nt & 1) == rank)
                        tma_2d_mc(sb + ps * XS_BYTES, &tm_x, (nt >> 1) * 64, qb * 512 + rank * 256, sb + FULL_BAR + 8 * ps, 3);
                    if (!(nt & 1)) {
                        const uint32_t wd = sb + WBUF + ((nt >> 1) % 3) * WS_BYTES;
                        tma_4d(wd, &tm_wa, 0, (nt >> 1) * 64, head, 0, sb + FULL_BAR + 8 * ps);
                        tma_4d(wd + 6144, &tm_wb, 0, (nt >> 1) * 64, head, 0, sb + FULL_BAR + 8 * ps);
                    }
                }
                __syncwarp();
            }
            if (t == 0) STAMP(1);
        }
        wg_wait<0>();
        fence_regs(acc0); fence_regs(acc1);
        STAMP(2);

#pragma unroll
        for (int i = 0; i < 8; i++) { acc0[i] *= QSCALE; acc1[i] *= QSCALE; acc0[24 + i] *= QSCALE; acc1[24 + i] *= QSCALE; }
        row_norm_stats(acc0, acc1, lane, sb + STATS);
#pragma unroll
        for (int i = 0; i < 4; i++) {
            qa0[i] = pack_bf16(acc0[2 * i], acc0[2 * i + 1]);
            qa1[i] = pack_bf16(acc1[2 * i], acc1[2 * i + 1]);
            qb0[i] = pack_bf16(acc0[24 + 2 * i], acc0[24 + 2 * i + 1]);
            qb1[i] = pack_bf16(acc1[24 + 2 * i], acc1[24 + 2 * i + 1]);
        }
        uint32_t kv0[16], kv1[16];
#pragma unroll
        for (int i = 0; i < 8; i++) {
            kv0[i] = pack_bf16(acc0[8 + 2 * i], acc0[8 + 2 * i + 1]);
            kv0[8 + i] = pack_bf16(acc0[32 + 2 * i], acc0[32 + 2 * i + 1]);
            kv1[i] = pack_bf16(acc1[8 + 2 * i], acc1[8 + 2 * i + 1]);
            kv1[8 + i] = pack_bf16(acc1[32 + 2 * i], acc1[32 + 2 * i + 1]);
        }
        __syncthreads();
        const uint32_t ra = sb + KVA + wg * REC + (w4 * 16 + (lane & 15)) * 16 + (lane >> 4) * 1024, rb = ra + (KVB + 4 * REC - KVA);
        stmatrix_x4(ra, kv0[0], kv0[1], kv0[2], kv0[3]);
        stmatrix_x4(ra + 2048, kv0[4], kv0[5], kv0[6], kv0[7]);
        stmatrix_x4(rb, kv0[8], kv0[9], kv0[10], kv0[11]);
        stmatrix_x4(rb + 2048, kv0[12], kv0[13], kv0[14], kv0[15]);
        stmatrix_x4(ra + 4 * REC, kv1[0], kv1[1], kv1[2], kv1[3]);
        stmatrix_x4(ra + 4 * REC + 2048, kv1[4], kv1[5], kv1[6], kv1[7]);
        stmatrix_x4(rb + 4 * REC, kv1[8], kv1[9], kv1[10], kv1[11]);
        stmatrix_x4(rb + 4 * REC + 2048, kv1[12], kv1[13], kv1[14], kv1[15]);
        uint8_t* const op = sp + KVA + (tid >> 6) * REC + 4096 + (tid & 63) * 16;
        *reinterpret_cast<uint4*>(op) = make_uint4(0x3f803f80u, 0x3f803f80u, 0x3f803f80u, 0x3f803f80u);
        *reinterpret_cast<uint4*>(op + (KVB + 4 * REC - KVA)) = make_uint4(0x3f803f80u, 0x3f803f80u, 0x3f803f80u, 0x3f803f80u);
        fence_async_smem();
        __syncthreads();
    }
    if (tid == 384) {
        uint8_t* dst = g_kv + (size_t)slot * 61440;
        bulk_s2g(dst, sb + KVA, 8 * REC);
        bulk_s2g(dst + 8 * REC, sb + KVB + 8 * REC, 4 * REC);
        asm volatile("cp.async.bulk.commit_group;" ::: "memory");
    }
    __syncwarp();
    STAMP(3);

    const uint32_t one2 = *reinterpret_cast<volatile uint32_t*>(sp + REDO + 16);
    const uint32_t caddr = sb + CONSTS;
    const float* st = reinterpret_cast<const float*>(sp + STATS);
    __nv_bfloat16* const obase = g_ocat + (size_t)(qb * 512 + wg * 64 + w4 * 16 + (lane >> 2)) * 1024 + head * 16 + 2 * (lane & 3);
    uint32_t* const redo_s = reinterpret_cast<uint32_t*>(sp + REDO) + wg;
    Scores S;
    float O[12];
    auto load_q = [&](uint32_t (&q)[4], int job) {
        asm volatile("ld.global.v4.u32 {%0, %1, %2, %3}, [%4];" : "=r"(q[0]), "=r"(q[1]), "=r"(q[2]), "=r"(q[3]) : "l"(qs + job * 512) : "memory");
    };
    auto finish = [&](uint32_t bit, __nv_bfloat16* dst) {
        if (!store_o(O, dst)) atomicOr(redo_s, bit);
    };
    auto save_q = [&](const uint32_t (&q)[4], int job) { qs[job * 512] = make_uint4(q[0], q[1], q[2], q[3]); };
    save_q(qb0, 2);
    const bool fast = shift_free_ok(st[0], st[1]) && shift_free_ok(st[2], st[3]);
    uint32_t redo = fast ? 0 : 15;
    {
        const uint32_t kd = dKB + (wg + 4) * RECD, vd = dVB + (wg + 4) * RECD;
        if (fast) {
#pragma unroll
            for (int i = 0; i < 8; i++) S.m[i] = 0.f;
#pragma unroll
            for (int i = 0; i < 6; i++) load_magic(S, i, caddr);
            zero_o(O);
            fence_regs(S.m); fence_regs(S.p);
            wg_fence();
            issue_qk(S, qb1, kd);
            wg_commit();
            wg_wait<0>();
            fence_regs(S.m); fence_regs(S.p);
            attn_step<2, true>(S, O, qb1, kd + RECD, vd, one2, caddr);
            attn_run<1>(S, O, qb1, vd + RECD, 3, one2, caddr);
        }
        if (tid == 384) {
            const unsigned long long fv = ((unsigned long long)__float_as_uint(st[3]) << 32) | __float_as_uint(st[1]) | 1u;
            STAMPK(4);
            asm volatile("cp.async.bulk.wait_group 0;" ::: "memory");
            STAMPK(5);
            asm volatile("st.relaxed.gpu.global.u64 [%0], %1;" ::"l"(g_flag + slot), "l"(fv) : "memory");
            STAMPK(6);
            STAMPH(9);
            STAMPKW();
        }
        __syncwarp();
        save_q(qb1, 3);
        if (fast) {
            attn_step<1, true>(S, O, qa0, dKA, vd + 4 * RECD, one2, caddr);
            finish(8, obase + 256 * 1024 + 512);
        }
    }
    STAMP(4);
    {
        const int os = head * 4 + ((qb + wg + 1) & 3);
        const bool fetcher = w4 == 0 && wg < 3;
        auto poll = [&]() -> unsigned long long {
            unsigned long long f;
            asm volatile("ld.relaxed.gpu.global.u64 %0, [%1];" : "=l"(f) : "l"(g_flag + os) : "memory");
            return f;
        };
        if (fast) {
            zero_o(O);
            attn_step<0, true>(S, O, qa0, dKA + RECD, dVA, one2, caddr);
            attn_step<0, true>(S, O, qa0, dKA + 2 * RECD, dVA + RECD, one2, caddr);
        }
        unsigned long long f = 0;
        if (fetcher) f = poll();
        if (fast) {
            attn_step<0, true>(S, O, qa0, dKA + 3 * RECD, dVA + 2 * RECD, one2, caddr);
            attn_step<0, true>(S, O, qa0, dKA + 4 * RECD, dVA + 3 * RECD, one2, caddr);
        }
        if (fetcher && lane == 0) {
            STAMPK(0);
#pragma unroll 1
            for (uint32_t i = 0; !f && i < (1u << 22); i++) f = poll();
            if (!f) __trap();
            STAMPK(1);
            asm volatile("fence.acquire.gpu;" ::: "memory");
            asm volatile("fence.proxy.async.global;" ::: "memory");
            STAMPK(2);
            const bool halo = wg == 2 && qb > 0;
            *reinterpret_cast<unsigned long long*>(sp + STATS + (wg + 1) * 16) = f;
            mbar_expect_tx(sb + X_BAR, halo ? 12 * REC : 8 * REC);
            const uint8_t* src = g_kv + (size_t)os * 61440;
            bulk_g2s(sb + KVA + (wg + 1) * 8 * REC, src, 8 * REC, sb + X_BAR);
            if (halo) bulk_g2s(sb + KVB, src + 8 * REC, 4 * REC, sb + X_BAR);
            STAMPK(3);
            if (wg == 1) STAMPH(10);
            STAMPKW();
        }
        __syncwarp();
        if (fast) {
            attn_step<0, true>(S, O, qa0, dKA + 5 * RECD, dVA + 4 * RECD, one2, caddr);
            attn_step<0, true>(S, O, qa0, dKA + 6 * RECD, dVA + 5 * RECD, one2, caddr);
        }
        if (fast) {
            attn_step<0, true>(S, O, qa0, dKA + 7 * RECD, dVA + 6 * RECD, one2, caddr);
            attn_step<0, true>(S, O, qa1, dKA, dVA + 7 * RECD, one2, caddr);
#pragma unroll
            for (int i = 0; i < 3; i++)
                qs[(4 + i) * 512] = make_uint4(__float_as_uint(O[4 * i]), __float_as_uint(O[4 * i + 1]), __float_as_uint(O[4 * i + 2]), __float_as_uint(O[4 * i + 3]));
        }
    }
    save_q(qa0, 0);
    STAMP(11);
    const int first = qb > 0 ? 0 : 4 - wg;
    {
        if (fast) {
            zero_o(O);
            attn_run<2>(S, O, qa1, dVA, 6, one2, caddr);
        }
        mbar_wait(sb + X_BAR, 0);
        STAMP(12);
        save_q(qa1, 1);
        if (!shift_free_ok(st[0], fmaxf(st[4], fmaxf(st[8], st[12])), (st[4] + st[8] + st[12]) >= 0.f)) redo |= 3;
        if (!shift_free_ok(st[2], st[13])) redo |= 4;
        if (fast) {
            attn_run<2>(S, O, qa1, dVA + 6 * RECD, 24, one2, caddr);
            load_q(qb0, 2);
            attn_step<0, true>(S, O, qa1, dKA + 31 * RECD, dVA + 30 * RECD, one2, caddr);
            attn_step<0, true>(S, O, qb0, dKB + (wg + first) * RECD, dVA + 31 * RECD, one2, caddr);
            finish(2, obase + 256 * 1024);
        }
    }
    STAMP(5);
    if (fast) {
        uint32_t vd = dVB + (wg + first) * RECD;
        zero_o(O);
        if (qb > 0) { attn_step<2, true>(S, O, qb0, vd + RECD + (dKA - dVA), vd, one2, caddr); vd += RECD; }
        load_q(qa0, 0);
        attn_run<1>(S, O, qb0, vd, qb > 0 ? 3 : wg, one2, caddr);
        attn_step<1, true>(S, O, qa0, dKA + 8 * RECD, dVB + (wg + 4) * RECD, one2, caddr);
        finish(4, obase + 512);
    }
    STAMP(6);
    asm volatile("griddepcontrol.launch_dependents;" ::: "memory");
    if (fast) {
#pragma unroll
        for (int i = 0; i < 3; i++)
            asm volatile("ld.global.v4.f32 {%0, %1, %2, %3}, [%4];" : "=f"(O[4 * i]), "=f"(O[4 * i + 1]), "=f"(O[4 * i + 2]), "=f"(O[4 * i + 3]) : "l"(qs + (4 + i) * 512) : "memory");
        attn_run<2>(S, O, qa0, dVA + 8 * RECD, 22, one2, caddr);
        attn_step<0, true>(S, O, qa0, dKA + 31 * RECD, dVA + 30 * RECD, one2, caddr);
        attn_step<0, false>(S, O, qa0, 0, dVA + 31 * RECD, one2, caddr);
        finish(1, obase);
    }
    STAMP(7);
    asm volatile("bar.sync %0, 128;" ::"r"(wg + 1) : "memory");
    redo = __shfl_sync(~0u, redo | *reinterpret_cast<volatile uint32_t*>(redo_s), 0);
#pragma unroll 1
    for (int job = 0; redo >> job; job++) {
        if (!((redo >> job) & 1)) continue;
        const uint4 qv = qs[job * 512];
        const uint32_t q[4] = {qv.x, qv.y, qv.z, qv.w};
        const int f0 = job == 2 ? first : 0;
        const uint32_t off = (wg + (job & 1) * 4 + f0) * RECD;
        const bool isb = job >= 2;
        attn_slow(O, q, isb ? dKB + off : dKA, isb ? dVB + off : dVA, isb ? 5 - f0 : 32, isb && f0 == 0, isb);
        store_o(O, obase + (job & 1) * 256 * 1024 + (isb ? 512 : 0));
    }
}

constexpr int NSTG2 = 9, NKB2 = 16;
constexpr uint32_t STG2_BYTES = 24576, BARS2 = NSTG2 * STG2_BYTES, SMEM2_BYTES = BARS2 + 256;

__global__ void __launch_bounds__(256, 1)
out_proj_kernel(const __grid_constant__ CUtensorMap tm_o, const __grid_constant__ CUtensorMap tm_woa,
                const __grid_constant__ CUtensorMap tm_wob, __nv_bfloat16* __restrict__ out) {
    extern __shared__ __align__(1024) uint8_t sp[];
    const uint32_t sb = smem_u32(sp);
    if ((sb & 0x3FFFF) != SMEM_BASE) __trap();
    const int tid = threadIdx.x, lane = tid & 31;
    const int warp = __shfl_sync(~0u, tid >> 5, 0), wg = warp >> 2;
    STAMP2(0);
    const int bid = blockIdx.x, rank = bid & 1, m0 = (bid >> 3) * 128, n0 = (bid & 7) * 64;
    const uint32_t FULL = sb + BARS2, EMPTY = sb + BARS2 + 8 * NSTG2;
    if (tid == 0) {
        for (int s = 0; s < NSTG2; s++) { mbar_init(FULL + 8 * s, 1); mbar_init(EMPTY + 8 * s, 4); }
        asm volatile("fence.mbarrier_init.release.cluster;" ::: "memory");
        for (int s = 0; s < NSTG2; s++) {
            mbar_expect_tx(FULL + 8 * s, STG2_BYTES);
            tma_2d(sb + s * STG2_BYTES + 16384, s < 8 ? &tm_woa : &tm_wob, n0, (s & 7) * 64, FULL + 8 * s);
        }
    }
    __syncwarp();
    cluster_sync();
    asm volatile("griddepcontrol.wait;" ::: "memory");
    STAMP2(1);
    if (tid == 0) {
        for (int s = 0; s < NSTG2; s++) tma_2d_mc(sb + s * STG2_BYTES + rank * 8192, &tm_o, s * 64, m0 + rank * 64, FULL + 8 * s, 3);
        g_flag[bid] = 0;
    }
    const int row = m0 + warp * 16 + (lane >> 2);
    const float g0 = g_gate[row], g1 = g_gate[row + 8];
    float accA[32], accB[32];
#pragma unroll
    for (int i = 0; i < 32; i++) { accA[i] = 0.f; accB[i] = 0.f; }
    fence_regs(accA); fence_regs(accB);
    const uint64_t da0 = make_desc(SMEM_BASE + wg * 8192, 16, 1024, 1), db0 = make_desc(SMEM_BASE + 16384, 8192, 1024, 1);
#pragma unroll
    for (int kb = 0; kb < NKB2; kb++) {
        const int s = kb % NSTG2;
        mbar_wait(FULL + 8 * s, (kb / NSTG2) & 1);
        const uint64_t da = da0 + (uint64_t)(s * (STG2_BYTES >> 4)), db = db0 + (uint64_t)(s * (STG2_BYTES >> 4));
        wg_fence();
#pragma unroll
        for (int k = 0; k < 4; k++) {
            if (kb < 8) wgmma_ss_n64_tb(accA, da + 2 * k, db + 128 * k);
            else wgmma_ss_n64_tb(accB, da + 2 * k, db + 128 * k);
        }
        wg_commit();
        if (kb >= 1 && kb - 1 + NSTG2 < NKB2) {
            wg_wait<1>();
            const int ps = (kb - 1) % NSTG2;
            if ((tid & 127) == 32 || (tid & 127) == 64) mbar_arrive_cluster(EMPTY + 8 * ps, (tid >> 6) & 1);
            if (tid == 0) {
                const int nk = kb - 1 + NSTG2;
                mbar_wait(EMPTY + 8 * ps, 0);
                mbar_expect_tx(FULL + 8 * ps, STG2_BYTES);
                tma_2d_mc(sb + ps * STG2_BYTES + rank * 8192, &tm_o, nk * 64, m0 + rank * 64, FULL + 8 * ps, 3);
                tma_2d(sb + ps * STG2_BYTES + 16384, &tm_wob, n0, (nk & 7) * 64, FULL + 8 * ps);
            }
            __syncwarp();
        }
    }
    wg_wait<0>();
    fence_regs(accA); fence_regs(accB);
    STAMP2(2);
    __syncthreads();
    const uint32_t tile = sb + 7 * STG2_BYTES + warp * 2048;
    const int mrow = (lane & 7) + ((lane >> 3) & 1) * 8;
#pragma unroll
    for (int p = 0; p < 4; p++) {
        uint32_t r[4];
#pragma unroll
        for (int h = 0; h < 2; h++) {
            const int i = (2 * p + h) * 4;
            r[2 * h] = pack_bf16(g0 * accA[i] + (1.f - g0) * accB[i], g0 * accA[i + 1] + (1.f - g0) * accB[i + 1]);
            r[2 * h + 1] = pack_bf16(g1 * accA[i + 2] + (1.f - g1) * accB[i + 2], g1 * accA[i + 3] + (1.f - g1) * accB[i + 3]);
        }
        const int chunk = 2 * p + (lane >> 4);
        stmatrix_x4(tile + mrow * 128 + ((chunk ^ (mrow & 7)) << 4), r[0], r[1], r[2], r[3]);
    }
    __syncwarp();
#pragma unroll
    for (int p = 0; p < 4; p++) {
        const int r = p * 4 + (lane >> 3), c = lane & 7;
        const uint4 v = *reinterpret_cast<const uint4*>(sp + 7 * STG2_BYTES + warp * 2048 + r * 128 + ((c ^ (r & 7)) << 4));
        *reinterpret_cast<uint4*>(out + (size_t)(m0 + warp * 16 + r) * DM + n0 + c * 8) = v;
    }
    STAMP2(3);
}

typedef CUresult (*EncodeFn)(CUtensorMap*, CUtensorMapDataType, cuuint32_t, void*, const cuuint64_t*, const cuuint64_t*,
                             const cuuint32_t*, const cuuint32_t*, CUtensorMapInterleave, CUtensorMapSwizzle,
                             CUtensorMapL2promotion, CUtensorMapFloatOOBfill);

void encode(EncodeFn fn, CUtensorMap* tm, const void* ptr, int rank, const cuuint64_t* dims, const cuuint64_t* strides,
            const cuuint32_t* box, CUtensorMapSwizzle swz) {
    const cuuint32_t es[4] = {1, 1, 1, 1};
    fn(tm, CU_TENSOR_MAP_DATA_TYPE_BFLOAT16, rank, const_cast<void*>(ptr), dims, strides, box, es, CU_TENSOR_MAP_INTERLEAVE_NONE,
       swz, CU_TENSOR_MAP_L2_PROMOTION_L2_256B, CU_TENSOR_MAP_FLOAT_OOB_FILL_NONE);
}

}

extern "C" void kernel_launch(void* const* d_in, const int* in_sizes, int n_in, void* d_out, int out_size) {
    (void)in_sizes; (void)n_in; (void)out_size;
    const __nv_bfloat16* x = (const __nv_bfloat16*)d_in[0];
    const __nv_bfloat16* gate_w = (const __nv_bfloat16*)d_in[6];
    static EncodeFn fn = nullptr;
    static void* ocat = nullptr;
    if (!fn) {
        cudaDriverEntryPointQueryResult qr;
        cudaGetDriverEntryPoint("cuTensorMapEncodeTiled", (void**)&fn, cudaEnableDefault, &qr);
        cudaGetSymbolAddress(&ocat, g_ocat);
        cudaFuncSetAttribute(qkv_attn_kernel, cudaFuncAttributeMaxDynamicSharedMemorySize, SMEM1_BYTES);
        cudaFuncSetAttribute(out_proj_kernel, cudaFuncAttributeMaxDynamicSharedMemorySize, SMEM2_BYTES);
    }
    CUtensorMap tm_x, tm_wa, tm_wb, tm_o, tm_woa, tm_wob;
    {
        const cuuint64_t dims[2] = {512, 2048}, str[1] = {1024};
        const cuuint32_t box[2] = {64, 256};
        encode(fn, &tm_x, x, 2, dims, str, box, CU_TENSOR_MAP_SWIZZLE_128B);
    }
    {
        const cuuint64_t dims[4] = {16, 512, 32, 3}, str[3] = {3072, 32, 1024};
        const cuuint32_t box[4] = {16, 64, 1, 3};
        encode(fn, &tm_wa, d_in[1], 4, dims, str, box, CU_TENSOR_MAP_SWIZZLE_32B);
        encode(fn, &tm_wb, d_in[4], 4, dims, str, box, CU_TENSOR_MAP_SWIZZLE_32B);
    }
    {
        const cuuint64_t dims[2] = {1024, 2048}, str[1] = {2048};
        const cuuint32_t box[2] = {64, 64};
        encode(fn, &tm_o, ocat, 2, dims, str, box, CU_TENSOR_MAP_SWIZZLE_128B);
    }
    {
        const cuuint64_t dims[2] = {512, 512}, str[1] = {1024};
        const cuuint32_t box[2] = {64, 64};
        encode(fn, &tm_woa, d_in[2], 2, dims, str, box, CU_TENSOR_MAP_SWIZZLE_128B);
        encode(fn, &tm_wob, d_in[5], 2, dims, str, box, CU_TENSOR_MAP_SWIZZLE_128B);
    }
    cudaLaunchAttribute at[2];
    at[0].id = cudaLaunchAttributeClusterDimension;
    at[0].val.clusterDim.x = 2; at[0].val.clusterDim.y = 1; at[0].val.clusterDim.z = 1;
    at[1].id = cudaLaunchAttributeProgrammaticStreamSerialization;
    at[1].val.programmaticStreamSerializationAllowed = 1;
    cudaLaunchConfig_t cfg = {};
    cfg.gridDim = dim3(128); cfg.blockDim = dim3(512); cfg.dynamicSmemBytes = SMEM1_BYTES;
    cfg.stream = cudaStreamPerThread; cfg.attrs = at; cfg.numAttrs = 1;
    cudaLaunchKernelEx(&cfg, qkv_attn_kernel, tm_x, tm_wa, tm_wb, x, gate_w);
    cfg.blockDim = dim3(256); cfg.dynamicSmemBytes = SMEM2_BYTES; cfg.numAttrs = 2;
    cudaLaunchKernelEx(&cfg, out_proj_kernel, tm_o, tm_woa, tm_wob, (__nv_bfloat16*)d_out);
}
```

```cpp
#include <cuda_runtime.h>
#include <cuda_bf16.h>
#include <cuda.h>
#include <stdint.h>

namespace {

constexpr int SEQ = 2048, DM = 512;

__device__ __align__(1024) uint8_t g_kv[128 * 61440];
__device__ unsigned long long g_flag[128];
__device__ uint32_t g_cnt[2][4 * 32];
__device__ uint4 g_qsave[128 * 7 * 512];
__device__ float g_gate[SEQ];
__device__ __align__(1024) __nv_bfloat16 g_ocat[SEQ * 1024];

#define STAMP(i)
#define STAMPH(i)
#define STAMPK(i)
#define STAMPKW()
#define STAMP2(i)

__device__ __forceinline__ uint32_t smem_u32(const void* p) { return (uint32_t)__cvta_generic_to_shared(p); }
__device__ __forceinline__ void wg_fence() { asm volatile("wgmma.fence.sync.aligned;" ::: "memory"); }
__device__ __forceinline__ void wg_commit() { asm volatile("wgmma.commit_group.sync.aligned;" ::: "memory"); }
template <int N> __device__ __forceinline__ void wg_wait() { asm volatile("wgmma.wait_group.sync.aligned %0;" ::"n"(N) : "memory"); }
constexpr uint32_t SMEM_BASE = 1024;
__host__ __device__ constexpr uint64_t make_desc(uint32_t addr, uint32_t lbo, uint32_t sbo, uint32_t mode) {
    return (uint64_t)((addr & 0x3FFFF) >> 4) | ((uint64_t)(lbo >> 4) << 16) | ((uint64_t)(sbo >> 4) << 32) | ((uint64_t)mode << 62);
}
template <int N> __device__ __forceinline__ void fence_regs(float (&r)[N]) {
#pragma unroll
    for (int i = 0; i < N; i++) asm volatile("" : "+f"(r[i])::"memory");
}
template <int N> __device__ __forceinline__ void fence_regs(uint32_t (&r)[N]) {
#pragma unroll
    for (int i = 0; i < N; i++) asm volatile("" : "+r"(r[i])::"memory");
}
__device__ __forceinline__ void mbar_init(uint32_t bar, uint32_t count) {
    asm volatile("mbarrier.init.shared::cta.b64 [%0], %1;" ::"r"(bar), "r"(count) : "memory");
}
__device__ __forceinline__ void mbar_expect_tx(uint32_t bar, uint32_t bytes) {
    asm volatile("mbarrier.arrive.expect_tx.shared::cta.b64 _, [%0], %1;" ::"r"(bar), "r"(bytes) : "memory");
}
__device__ __forceinline__ void mbar_arrive_cluster(uint32_t bar, uint32_t cta) {
    asm volatile("{\n.reg .b32 ra;\nmapa.shared::cluster.u32 ra, %0, %1;\n"
                 "mbarrier.arrive.shared::cluster.b64 _, [ra];\n}\n" ::"r"(bar), "r"(cta) : "memory");
}
__device__ __forceinline__ bool mbar_try(uint32_t bar, uint32_t parity) {
    uint32_t ok;
    asm volatile("{\n.reg .pred p;\nmbarrier.try_wait.parity.shared::cta.b64 p, [%1], %2;\nselp.u32 %0, 1, 0, p;\n}\n"
                 : "=r"(ok) : "r"(bar), "r"(parity) : "memory");
    return ok != 0;
}
__device__ __forceinline__ void mbar_wait(uint32_t bar, uint32_t parity) {
    if (mbar_try(bar, parity)) return;
#pragma unroll 1
    for (uint32_t i = 0; i < (1u << 22); i++)
        if (mbar_try(bar, parity)) return;
    __trap();
}
__device__ __forceinline__ void mbar_wait_warp(uint32_t bar, uint32_t parity) {
    if (__all_sync(~0u, mbar_try(bar, parity))) return;
#pragma unroll 1
    for (uint32_t i = 0; i < (1u << 22); i++)
        if (__all_sync(~0u, mbar_try(bar, parity))) return;
    __trap();
}
template <int ID, int N> __device__ __forceinline__ void named_sync() { asm volatile("bar.sync %0, %1;" ::"n"(ID), "n"(N) : "memory"); }
__device__ __forceinline__ void fence_async_smem() { asm volatile("fence.proxy.async.shared::cta;" ::: "memory"); }
__device__ __forceinline__ void tma_2d(uint32_t dst, const CUtensorMap* tm, int c0, int c1, uint32_t bar) {
    asm volatile("cp.async.bulk.tensor.2d.shared::cluster.global.mbarrier::complete_tx::bytes [%0], [%1, {%3, %4}], [%2];"
                 ::"r"(dst), "l"(tm), "r"(bar), "r"(c0), "r"(c1) : "memory");
}
__device__ __forceinline__ void tma_2d_mc(uint32_t dst, const CUtensorMap* tm, int c0, int c1, uint32_t bar, uint16_t mask) {
    asm volatile("cp.async.bulk.tensor.2d.shared::cluster.global.mbarrier::complete_tx::bytes.multicast::cluster [%0], [%1, {%3, %4}], [%2], %5;"
                 ::"r"(dst), "l"(tm), "r"(bar), "r"(c0), "r"(c1), "h"(mask) : "memory");
}
__device__ __forceinline__ void tma_3d(uint32_t dst, const CUtensorMap* tm, int c0, int c1, int c2, uint32_t bar) {
    asm volatile("cp.async.bulk.tensor.3d.shared::cluster.global.mbarrier::complete_tx::bytes [%0], [%1, {%3, %4, %5}], [%2];"
                 ::"r"(dst), "l"(tm), "r"(bar), "r"(c0), "r"(c1), "r"(c2) : "memory");
}
__device__ __forceinline__ void mbar_arrive(uint32_t bar) {
    asm volatile("mbarrier.arrive.shared::cta.b64 _, [%0];" ::"r"(bar) : "memory");
}
__device__ __forceinline__ void tma_4d(uint32_t dst, const CUtensorMap* tm, int c0, int c1, int c2, int c3, uint32_t bar) {
    asm volatile("cp.async.bulk.tensor.4d.shared::cluster.global.mbarrier::complete_tx::bytes [%0], [%1, {%3, %4, %5, %6}], [%2];"
                 ::"r"(dst), "l"(tm), "r"(bar), "r"(c0), "r"(c1), "r"(c2), "r"(c3) : "memory");
}
__device__ __forceinline__ void bulk_g2s(uint32_t dst, const void* src, uint32_t bytes, uint32_t bar) {
    asm volatile("cp.async.bulk.shared::cluster.global.mbarrier::complete_tx::bytes [%0], [%1], %2, [%3];"
                 ::"r"(dst), "l"(src), "r"(bytes), "r"(bar) : "memory");
}
__device__ __forceinline__ void bulk_s2g(void* dst, uint32_t src, uint32_t bytes) {
    asm volatile("cp.async.bulk.global.shared::cta.bulk_group [%0], [%1], %2;" ::"l"(dst), "r"(src), "r"(bytes) : "memory");
}
__device__ __forceinline__ void stmatrix_x4(uint32_t addr, uint32_t r0, uint32_t r1, uint32_t r2, uint32_t r3) {
    asm volatile("stmatrix.sync.aligned.m8n8.x4.shared.b16 [%0], {%1, %2, %3, %4};" ::"r"(addr), "r"(r0), "r"(r1), "r"(r2), "r"(r3) : "memory");
}
__device__ __forceinline__ float ex2(float x) { float y; asm("ex2.approx.ftz.f32 %0, %1;" : "=f"(y) : "f"(x)); return y; }
__device__ __forceinline__ uint32_t pack_bf16(float lo, float hi) {
    uint32_t r; asm("cvt.rn.bf16x2.f32 %0, %1, %2;" : "=r"(r) : "f"(hi), "f"(lo)); return r;
}

__device__ __forceinline__ void wgmma_ss_n96_tb(float (&d)[48], uint64_t da, uint64_t db) {
    asm volatile("wgmma.mma_async.sync.aligned.m64n96k16.f32.bf16.bf16 {"
        "%0, %1, %2, %3, %4, %5, %6, %7, %8, %9, %10, %11, %12, %13, %14, %15 "
        "%16, %17, %18, %19, %20, %21, %22, %23, %24, %25, %26, %27, %28, %29, %30, %31 "
        "%32, %33, %34, %35, %36, %37, %38, %39, %40, %41, %42, %43, %44, %45, %46, %47}, "
        "%48, %49, 1, 1, 1, 0, 1;\n"
        : "+f"(d[0]), "+f"(d[1]), "+f"(d[2]), "+f"(d[3]), "+f"(d[4]), "+f"(d[5]), "+f"(d[6]), "+f"(d[7]),
          "+f"(d[8]), "+f"(d[9]), "+f"(d[10]), "+f"(d[11]), "+f"(d[12]), "+f"(d[13]), "+f"(d[14]), "+f"(d[15]),
          "+f"(d[16]), "+f"(d[17]), "+f"(d[18]), "+f"(d[19]), "+f"(d[20]), "+f"(d[21]), "+f"(d[22]), "+f"(d[23]),
          "+f"(d[24]), "+f"(d[25]), "+f"(d[26]), "+f"(d[27]), "+f"(d[28]), "+f"(d[29]), "+f"(d[30]), "+f"(d[31]),
          "+f"(d[32]), "+f"(d[33]), "+f"(d[34]), "+f"(d[35]), "+f"(d[36]), "+f"(d[37]), "+f"(d[38]), "+f"(d[39]),
          "+f"(d[40]), "+f"(d[41]), "+f"(d[42]), "+f"(d[43]), "+f"(d[44]), "+f"(d[45]), "+f"(d[46]), "+f"(d[47])
        : "l"(da), "l"(db));
}
__device__ __forceinline__ void wgmma_ss_n96_tb_zero(float (&d)[48], uint64_t da, uint64_t db) {
    asm volatile("wgmma.mma_async.sync.aligned.m64n96k16.f32.bf16.bf16 {"
        "%0, %1, %2, %3, %4, %5, %6, %7, %8, %9, %10, %11, %12, %13, %14, %15 "
        "%16, %17, %18, %19, %20, %21, %22, %23, %24, %25, %26, %27, %28, %29, %30, %31 "
        "%32, %33, %34, %35, %36, %37, %38, %39, %40, %41, %42, %43, %44, %45, %46, %47}, "
        "%48, %49, 0, 1, 1, 0, 1;\n"
        : "=f"(d[0]), "=f"(d[1]), "=f"(d[2]), "=f"(d[3]), "=f"(d[4]), "=f"(d[5]), "=f"(d[6]), "=f"(d[7]),
          "=f"(d[8]), "=f"(d[9]), "=f"(d[10]), "=f"(d[11]), "=f"(d[12]), "=f"(d[13]), "=f"(d[14]), "=f"(d[15]),
          "=f"(d[16]), "=f"(d[17]), "=f"(d[18]), "=f"(d[19]), "=f"(d[20]), "=f"(d[21]), "=f"(d[22]), "=f"(d[23]),
          "=f"(d[24]), "=f"(d[25]), "=f"(d[26]), "=f"(d[27]), "=f"(d[28]), "=f"(d[29]), "=f"(d[30]), "=f"(d[31]),
          "=f"(d[32]), "=f"(d[33]), "=f"(d[34]), "=f"(d[35]), "=f"(d[36]), "=f"(d[37]), "=f"(d[38]), "=f"(d[39]),
          "=f"(d[40]), "=f"(d[41]), "=f"(d[42]), "=f"(d[43]), "=f"(d[44]), "=f"(d[45]), "=f"(d[46]), "=f"(d[47])
        : "l"(da), "l"(db));
}
__device__ __forceinline__ void wgmma_ss_n64_tb(float (&d)[32], uint64_t da, uint64_t db) {
    asm volatile("wgmma.mma_async.sync.aligned.m64n64k16.f32.bf16.bf16 {"
        "%0, %1, %2, %3, %4, %5, %6, %7, %8, %9, %10, %11, %12, %13, %14, %15 "
        "%16, %17, %18, %19, %20, %21, %22, %23, %24, %25, %26, %27, %28, %29, %30, %31}, "
        "%32, %33, 1, 1, 1, 0, 1;\n"
        : "+f"(d[0]), "+f"(d[1]), "+f"(d[2]), "+f"(d[3]), "+f"(d[4]), "+f"(d[5]), "+f"(d[6]), "+f"(d[7]),
          "+f"(d[8]), "+f"(d[9]), "+f"(d[10]), "+f"(d[11]), "+f"(d[12]), "+f"(d[13]), "+f"(d[14]), "+f"(d[15]),
          "+f"(d[16]), "+f"(d[17]), "+f"(d[18]), "+f"(d[19]), "+f"(d[20]), "+f"(d[21]), "+f"(d[22]), "+f"(d[23]),
          "+f"(d[24]), "+f"(d[25]), "+f"(d[26]), "+f"(d[27]), "+f"(d[28]), "+f"(d[29]), "+f"(d[30]), "+f"(d[31])
        : "l"(da), "l"(db));
}
template <uint32_t HI>
__device__ __forceinline__ void wgmma_rs_n64_zero(float (&d)[32], uint32_t a0, uint32_t a1, uint32_t a2, uint32_t a3, uint32_t db_lo) {
    asm volatile("{\n.reg .b64 dsc;\nmov.b64 dsc, {%36, %37};\n"
        "wgmma.mma_async.sync.aligned.m64n64k16.f32.bf16.bf16 {"
        "%0, %1, %2, %3, %4, %5, %6, %7, %8, %9, %10, %11, %12, %13, %14, %15 "
        "%16, %17, %18, %19, %20, %21, %22, %23, %24, %25, %26, %27, %28, %29, %30, %31}, "
        "{%32, %33, %34, %35}, dsc, 0, 1, 1, 0;\n}\n"
        : "+f"(d[0]), "+f"(d[1]), "+f"(d[2]), "+f"(d[3]), "+f"(d[4]), "+f"(d[5]), "+f"(d[6]), "+f"(d[7]),
          "+f"(d[8]), "+f"(d[9]), "+f"(d[10]), "+f"(d[11]), "+f"(d[12]), "+f"(d[13]), "+f"(d[14]), "+f"(d[15]),
          "+f"(d[16]), "+f"(d[17]), "+f"(d[18]), "+f"(d[19]), "+f"(d[20]), "+f"(d[21]), "+f"(d[22]), "+f"(d[23]),
          "+f"(d[24]), "+f"(d[25]), "+f"(d[26]), "+f"(d[27]), "+f"(d[28]), "+f"(d[29]), "+f"(d[30]), "+f"(d[31])
        : "r"(a0), "r"(a1), "r"(a2), "r"(a3), "r"(db_lo), "n"(HI));
}
__device__ __forceinline__ void wgmma_rs_n24_tb64(float (&d)[12], uint32_t a0, uint32_t a1, uint32_t a2, uint32_t a3, uint64_t db) {
    asm volatile("wgmma.mma_async.sync.aligned.m64n24k16.f32.bf16.bf16 {"
        "%0, %1, %2, %3, %4, %5, %6, %7, %8, %9, %10, %11}, "
        "{%12, %13, %14, %15}, %16, 1, 1, 1, 1;\n"
        : "+f"(d[0]), "+f"(d[1]), "+f"(d[2]), "+f"(d[3]), "+f"(d[4]), "+f"(d[5]), "+f"(d[6]), "+f"(d[7]),
          "+f"(d[8]), "+f"(d[9]), "+f"(d[10]), "+f"(d[11])
        : "r"(a0), "r"(a1), "r"(a2), "r"(a3), "l"(db));
}
__device__ __forceinline__ void wgmma_rs_n16_zero64(float (&d)[8], uint32_t a0, uint32_t a1, uint32_t a2, uint32_t a3, uint64_t db) {
    asm volatile("wgmma.mma_async.sync.aligned.m64n16k16.f32.bf16.bf16 {"
        "%0, %1, %2, %3, %4, %5, %6, %7}, "
        "{%8, %9, %10, %11}, %12, 0, 1, 1, 0;\n"
        : "+f"(d[0]), "+f"(d[1]), "+f"(d[2]), "+f"(d[3]), "+f"(d[4]), "+f"(d[5]), "+f"(d[6]), "+f"(d[7])
        : "r"(a0), "r"(a1), "r"(a2), "r"(a3), "l"(db));
}
__device__ __forceinline__ void wgmma_rs_n48_64(float (&d)[24], uint32_t a0, uint32_t a1, uint32_t a2, uint32_t a3, uint64_t db) {
    asm volatile("wgmma.mma_async.sync.aligned.m64n48k16.f32.bf16.bf16 {"
        "%0, %1, %2, %3, %4, %5, %6, %7, %8, %9, %10, %11, %12, %13, %14, %15 "
        "%16, %17, %18, %19, %20, %21, %22, %23}, "
        "{%24, %25, %26, %27}, %28, 1, 1, 1, 0;\n"
        : "+f"(d[0]), "+f"(d[1]), "+f"(d[2]), "+f"(d[3]), "+f"(d[4]), "+f"(d[5]), "+f"(d[6]), "+f"(d[7]),
          "+f"(d[8]), "+f"(d[9]), "+f"(d[10]), "+f"(d[11]), "+f"(d[12]), "+f"(d[13]), "+f"(d[14]), "+f"(d[15]),
          "+f"(d[16]), "+f"(d[17]), "+f"(d[18]), "+f"(d[19]), "+f"(d[20]), "+f"(d[21]), "+f"(d[22]), "+f"(d[23])
        : "r"(a0), "r"(a1), "r"(a2), "r"(a3), "l"(db));
}
template <uint32_t HI>
__device__ __forceinline__ void wgmma_rs_n24_tb(float (&d)[12], uint32_t a0, uint32_t a1, uint32_t a2, uint32_t a3, uint32_t db_lo) {
    asm volatile("{\n.reg .b64 dsc;\nmov.b64 dsc, {%16, %17};\n"
        "wgmma.mma_async.sync.aligned.m64n24k16.f32.bf16.bf16 {"
        "%0, %1, %2, %3, %4, %5, %6, %7, %8, %9, %10, %11}, "
        "{%12, %13, %14, %15}, dsc, 1, 1, 1, 1;\n}\n"
        : "+f"(d[0]), "+f"(d[1]), "+f"(d[2]), "+f"(d[3]), "+f"(d[4]), "+f"(d[5]), "+f"(d[6]), "+f"(d[7]),
          "+f"(d[8]), "+f"(d[9]), "+f"(d[10]), "+f"(d[11])
        : "r"(a0), "r"(a1), "r"(a2), "r"(a3), "r"(db_lo), "n"(HI));
}

constexpr int NSLOT = 4, NSTEP = 16;
__host__ __device__ constexpr int step_half(int t) { return t < 3 ? 0 : (t > 12 ? 1 : (t & 1)); }
__host__ __device__ constexpr int step_kb(int t) { return t < 3 ? t : (t > 12 ? t - 8 : ((t & 1) ? (t - 3) / 2 : (t + 2) / 2)); }
constexpr uint32_t XS_BYTES = 32768, WS_BYTES = 12288, WBUF = NSLOT * XS_BYTES;
constexpr uint32_t REC = 5120, RECD = REC / 16, KVA = 0, KVB = 32 * REC, BARS = 28 * 8192;
static_assert(KVB + 12 * REC <= BARS && KVB == 20 * 8192, "layout");
constexpr uint32_t FULL_BAR = BARS, EMPTY_BAR = BARS + 40, X_BAR = BARS + 80,
                   MISC = BARS + 96,
                   STATS = BARS + 128,
                   CONSTS = BARS + 192,
                   P3BAR = BARS + 320,
                   CP_BAR = P3BAR + 38 * 8,
                   W_BAR = CP_BAR + 24;
constexpr uint32_t SMEM1_BYTES = W_BAR + 64;
static_assert(WBUF + 8 * WS_BYTES <= BARS, "ring too large");

constexpr uint32_t KHI = (uint32_t)(make_desc(0, 1024, 128, 0) >> 32), VHI = (uint32_t)(make_desc(0, 128, 1024, 0) >> 32);
constexpr uint32_t dKA = (uint32_t)make_desc(SMEM_BASE + KVA, 1024, 128, 0), dVA = (uint32_t)make_desc(SMEM_BASE + KVA + 2048, 128, 1024, 0);
constexpr uint32_t dKB = (uint32_t)make_desc(SMEM_BASE + KVB, 1024, 128, 0), dVB = (uint32_t)make_desc(SMEM_BASE + KVB + 2048, 128, 1024, 0);

constexpr float QSCALE = 0.25f * 1.4426950408889634f;
#define XMASK 0x0
#define AUNR 2
#define SRCORD 1
#define QKORD 2
constexpr float EXP_MAGIC = 381.401059f;

__device__ __forceinline__ uint32_t exp2_sw(float y0, float y1, uint32_t one2) {
    const uint32_t w = __byte_perm(__float_as_uint(y0), __float_as_uint(y1), 0x6521);
    uint32_t u, z;
    asm("lop3.b32 %0, %1, 0x007f007f, %2, 0xEA;" : "=r"(u) : "r"(w), "r"(one2));
    asm("fma.rn.bf16x2 %0, %1, %1, %2;" : "=r"(z) : "r"(u), "r"(0x40034003u));
    return w - u + z;
}

__device__ __forceinline__ void make_masks(uint32_t (&M)[9]) {
    uint32_t t;
    asm volatile("mov.u32 %0, %tid.x;" : "=r"(t));
    const int s0 = 16 - 16 * ((int)((t >> 1) & 48) + (int)((t >> 2) & 7) - 2 * (int)(t & 3));
    M[0] = 0; M[8] = 0xffffffffu;
#pragma unroll
    for (int i = 1; i < 8; i++) asm("shr.u32 %0, %1, %2;" : "=r"(M[i]) : "r"(0xffffffffu), "r"(max(s0 - 128 * (i - 7), 0)));
}

struct Scores { float m[8], p[24]; };

__device__ __forceinline__ void load_magic(Scores& S, int i, uint32_t caddr) {
    asm volatile("ld.volatile.shared.v4.f32 {%0, %1, %2, %3}, [%4];"
                 : "=f"(S.p[4 * i]), "=f"(S.p[4 * i + 1]), "=f"(S.p[4 * i + 2]), "=f"(S.p[4 * i + 3]) : "r"(caddr + 16 * i));
}
__device__ __forceinline__ void issue_qk(Scores& S, const uint32_t (&q)[4], uint32_t kd) {
    uint64_t kd64;
    asm("mov.b64 %0, {%1, %2};" : "=l"(kd64) : "r"(kd), "n"(KHI));
    if (QKORD & 1) wgmma_rs_n48_64(S.p, q[0], q[1], q[2], q[3], kd64 + 16);
    wgmma_rs_n16_zero64(S.m, q[0], q[1], q[2], q[3], kd64);
    if (!(QKORD & 1)) wgmma_rs_n48_64(S.p, q[0], q[1], q[2], q[3], kd64 + 16);
}

template <int MODE, bool QK>
__device__ __forceinline__ void attn_step(Scores& S, float (&O)[12], const uint32_t (&qn)[4], uint32_t kd_next, uint32_t vd,
                                          uint32_t one2, uint32_t caddr) {
    uint32_t P[16], M[9];
    if (MODE) make_masks(M);
    if (SRCORD == 1) {
#pragma unroll
        for (int i = 0; i < 4; i++) P[i] = pack_bf16(ex2(S.m[2 * i]), ex2(S.m[2 * i + 1]));
    }
#pragma unroll
    for (int ii = 0; ii < 6; ii++) {
        const int i = SRCORD == 3 ? 5 - ii : ii;
        if ((SRCORD == 0 || SRCORD == 3) && ii < 2) P[2 * ii] = pack_bf16(ex2(S.m[4 * ii]), ex2(S.m[4 * ii + 1]));
        if (SRCORD == 4 && ii >= 1 && ii < 5) P[ii - 1] = pack_bf16(ex2(S.m[2 * ii - 2]), ex2(S.m[2 * ii - 1]));
#pragma unroll
        for (int h = 0; h < 2; h++) {
            const float y0 = S.p[4 * i + 2 * h], y1 = S.p[4 * i + 2 * h + 1];
            P[4 + 2 * i + h] = ((XMASK >> (2 * i + h)) & 1) ? pack_bf16(ex2(y0), ex2(y1)) : exp2_sw(y0, y1, one2);
        }
        if (QK) load_magic(S, i, caddr);
        if ((SRCORD == 0 || SRCORD == 3) && ii < 2) P[2 * ii + 1] = pack_bf16(ex2(S.m[4 * ii + 2]), ex2(S.m[4 * ii + 3]));
    }
    if (SRCORD == 2) {
#pragma unroll
        for (int i = 0; i < 4; i++) P[i] = pack_bf16(ex2(S.m[2 * i]), ex2(S.m[2 * i + 1]));
    }
#pragma unroll
    for (int i = 0; i < 16; i++) {
        if (MODE == 1) P[i] &= M[(i & 1) - (i >> 1) + 7];
        if (MODE == 2) P[i] &= ~M[(i & 1) - (i >> 1) + 7];
    }
    uint64_t vd64;
    asm("mov.b64 %0, {%1, %2};" : "=l"(vd64) : "r"(vd), "n"(VHI));
    fence_regs(P); fence_regs(S.p);
    wg_fence();
    if (QK && QKORD < 2) issue_qk(S, qn, kd_next);
#pragma unroll
    for (int k = 0; k < 4; k++) wgmma_rs_n24_tb64(O, P[4 * k], P[4 * k + 1], P[4 * k + 2], P[4 * k + 3], vd64 + k * 16);
    if (QK && QKORD >= 2) issue_qk(S, qn, kd_next);
    wg_commit();
    wg_wait<0>();
    fence_regs(S.m); fence_regs(S.p); fence_regs(P); fence_regs(O);
}

template <int UNR>
__device__ __forceinline__ void attn_run(Scores& S, float (&O)[12], const uint32_t (&q)[4], uint32_t vd, int n, uint32_t one2, uint32_t caddr) {
#pragma unroll 1
    for (const uint32_t vend = vd + n * RECD; vd != vend; vd += UNR * RECD) {
#pragma unroll
        for (int u = 0; u < UNR; u++) attn_step<0, true>(S, O, q, vd + (u + 1) * RECD + (dKA - dVA), vd + u * RECD, one2, caddr);
    }
}
__device__ __forceinline__ void zero_o(float (&O)[12]) {
#pragma unroll
    for (int i = 0; i < 12; i++) O[i] = 0.f;
    fence_regs(O);
}

__device__ __forceinline__ void attn_slow(float (&O)[12], const uint32_t (&q)[4], uint32_t kd, uint32_t vd,
                                          int ntiles, bool mask_first, bool mask_last) {
    const int lane = threadIdx.x & 31;
    const int dbase = ((threadIdx.x >> 5) & 3) * 16 + (lane >> 2) - 2 * (lane & 3);
    uint32_t P[16];
    float S[32];
    float m0 = -INFINITY, m1 = -INFINITY;
#pragma unroll
    for (int i = 0; i < 32; i++) S[i] = 0.f;
#pragma unroll
    for (int i = 0; i < 12; i++) O[i] = 0.f;
#pragma unroll 1
    for (int j = 0; j < ntiles; j++) {
        fence_regs(S);
        wg_fence();
        wgmma_rs_n64_zero<KHI>(S, q[0], q[1], q[2], q[3], kd + j * RECD);
        wg_commit();
        wg_wait<0>();
        fence_regs(S);
        const bool mf = mask_first && j == 0, ml = mask_last && j == ntiles - 1;
        if (mf || ml) {
#pragma unroll
            for (int i = 0; i < 32; i++) {
                const int d = dbase + 8 * ((i >> 1) & 1) - 8 * (i >> 2) - (i & 1);
                const bool keep = ml ? (d >= 0) : (d < 0);
                if (!keep) S[i] = -1e9f * 1.4426950408889634f;
            }
        }
        float x0 = m0, x1 = m1;
#pragma unroll
        for (int b = 0; b < 8; b++) {
            x0 = fmaxf(x0, fmaxf(S[4 * b], S[4 * b + 1]));
            x1 = fmaxf(x1, fmaxf(S[4 * b + 2], S[4 * b + 3]));
        }
        x0 = fmaxf(x0, __shfl_xor_sync(~0u, x0, 1)); x0 = fmaxf(x0, __shfl_xor_sync(~0u, x0, 2));
        x1 = fmaxf(x1, __shfl_xor_sync(~0u, x1, 1)); x1 = fmaxf(x1, __shfl_xor_sync(~0u, x1, 2));
        const float a0 = ex2(m0 - x0), a1 = ex2(m1 - x1);
        m0 = x0; m1 = x1;
#pragma unroll
        for (int b = 0; b < 3; b++) { O[4 * b] *= a0; O[4 * b + 1] *= a0; O[4 * b + 2] *= a1; O[4 * b + 3] *= a1; }
#pragma unroll
        for (int b = 0; b < 8; b++) {
            P[2 * b] = pack_bf16(ex2(S[4 * b] - m0), ex2(S[4 * b + 1] - m0));
            P[2 * b + 1] = pack_bf16(ex2(S[4 * b + 2] - m1), ex2(S[4 * b + 3] - m1));
        }
        fence_regs(P); fence_regs(O);
        wg_fence();
#pragma unroll
        for (int k = 0; k < 4; k++) wgmma_rs_n24_tb<VHI>(O, P[4 * k], P[4 * k + 1], P[4 * k + 2], P[4 * k + 3], vd + j * RECD + k * 16);
        wg_commit();
        wg_wait<0>();
        fence_regs(P); fence_regs(O);
    }
}

__device__ __forceinline__ bool shift_free_ok(float q2, float k2, float vlo, float vhi) {
    float b;
    asm("sqrt.approx.f32 %0, %1;" : "=f"(b) : "f"(q2 * k2));
    b = b * 1.02f + 1.f;
    const float e = ex2(b);
    return __all_sync(~0u, b <= 110.f && vhi * e <= 0x1p114f && vlo * 0x1p99f >= e);
}

__device__ __forceinline__ void store_o(const float (&O)[12], __nv_bfloat16* dst  ) {
    float i0, i1;
    asm("rcp.approx.ftz.f32 %0, %1;" : "=f"(i0) : "f"(O[8]));
    asm("rcp.approx.ftz.f32 %0, %1;" : "=f"(i1) : "f"(O[10]));
    *reinterpret_cast<uint32_t*>(dst) = pack_bf16(O[0] * i0, O[1] * i0);
    *reinterpret_cast<uint32_t*>(dst + 8) = pack_bf16(O[4] * i0, O[5] * i0);
    *reinterpret_cast<uint32_t*>(dst + 8 * 1024) = pack_bf16(O[2] * i1, O[3] * i1);
    *reinterpret_cast<uint32_t*>(dst + 8 * 1024 + 8) = pack_bf16(O[6] * i1, O[7] * i1);
}

__device__ __forceinline__ uint32_t absmax8(const uint32_t* a, const uint32_t* b) {
    uint32_t m[4];
#pragma unroll
    for (int i = 0; i < 4; i++) asm("max.NaN.xorsign.abs.bf16x2 %0, %1, %2;" : "=r"(m[i]) : "r"(a[i]), "r"(b[i]));
    asm("max.NaN.xorsign.abs.bf16x2 %0, %1, %2;" : "=r"(m[0]) : "r"(m[0]), "r"(m[1]));
    asm("max.NaN.xorsign.abs.bf16x2 %0, %1, %2;" : "=r"(m[2]) : "r"(m[2]), "r"(m[3]));
    asm("max.NaN.xorsign.abs.bf16x2 %0, %1, %2;" : "=r"(m[0]) : "r"(m[0]), "r"(m[2]));
    return __reduce_max_sync(~0u, max(m[0] & 0x7fff0000u, (m[0] << 16) & 0x7fff0000u));
}
__device__ __forceinline__ uint32_t up16(uint32_t fbits) { return min(fbits >> 16, 0x7ffeu) + 1u; }

__device__ __forceinline__ void cnt_release(uint32_t* p, uint32_t n) { asm volatile("red.release.gpu.global.add.u32 [%0], %1;" ::"l"(p), "r"(n) : "memory"); }
__device__ __forceinline__ void cnt_wait_warp(const uint32_t* p, uint32_t target) {
#pragma unroll 1
    for (uint32_t i = 0; i < (1u << 22); i++) {
        uint32_t v;
        asm volatile("ld.relaxed.gpu.global.u32 %0, [%1];" : "=r"(v) : "l"(p) : "memory");
        if (__all_sync(~0u, ((v ^ target) & 0xfffffu) == 0)) { asm volatile("fence.acquire.gpu;" ::: "memory"); return; }
    }
    __trap();
}

__device__ __forceinline__ void row_norm_part(const float (&a)[48], int i, float& s0, float& s1) {
    const float* p = a + 24 * (i >> 1) + 8 * (i & 1);
    s0 = (p[0] * p[0] + p[1] * p[1]) + (p[4] * p[4] + p[5] * p[5]);
    s1 = (p[2] * p[2] + p[3] * p[3]) + (p[6] * p[6] + p[7] * p[7]);
}
__device__ __forceinline__ void row_norm_stats(const float (&s)[4][4], int lane, uint32_t stats_addr) {
    float t[4][2];
    const bool o1 = lane & 1, o2 = lane & 2;
#pragma unroll
    for (int i = 0; i < 4; i++) {
        t[i][0] = (o1 ? s[i][1] : s[i][0]) + __shfl_xor_sync(~0u, o1 ? s[i][0] : s[i][1], 1);
        t[i][1] = (o1 ? s[i][3] : s[i][2]) + __shfl_xor_sync(~0u, o1 ? s[i][2] : s[i][3], 1);
    }
    uint32_t m[4];
#pragma unroll
    for (int i = 0; i < 4; i++) {
        const float v = (o2 ? t[i][1] : t[i][0]) + __shfl_xor_sync(~0u, o2 ? t[i][0] : t[i][1], 2);
        m[i] = __float_as_uint(v);
    }
#pragma unroll
    for (int i = 0; i < 4; i++) m[i] = __reduce_max_sync(~0u, m[i]);
    const uint32_t mv = o2 ? (o1 ? m[3] : m[2]) : (o1 ? m[1] : m[0]);
    if (lane < 4) asm volatile("red.shared.max.u32 [%0], %1;" ::"r"(stats_addr + 4 * lane), "r"(mv) : "memory");
}
__device__ __forceinline__ void finish_branch(float (&a)[48], int br, float (&s)[4][4], int mt, uint32_t (&q)[4], uint32_t (&kv)[16]) {
#pragma unroll
    for (int i = 0; i < 8; i++) a[24 * br + i] *= QSCALE;
    row_norm_part(a, 2 * br, s[2 * br][2 * mt], s[2 * br][2 * mt + 1]);
    row_norm_part(a, 2 * br + 1, s[2 * br + 1][2 * mt], s[2 * br + 1][2 * mt + 1]);
#pragma unroll
    for (int i = 0; i < 4; i++) q[i] = pack_bf16(a[24 * br + 2 * i], a[24 * br + 2 * i + 1]);
#pragma unroll
    for (int i = 0; i < 8; i++) kv[8 * br + i] = pack_bf16(a[24 * br + 8 + 2 * i], a[24 * br + 8 + 2 * i + 1]);
}

__global__ void __launch_bounds__(512, 1)
fused_kernel(const __grid_constant__ CUtensorMap tm_x, const __grid_constant__ CUtensorMap tm_wa,
             const __grid_constant__ CUtensorMap tm_wb,
             const __grid_constant__ CUtensorMap tm_woa4, const __grid_constant__ CUtensorMap tm_wob4,
             const __grid_constant__ CUtensorMap tm_o1, const __grid_constant__ CUtensorMap tm_o4,
             const __nv_bfloat16* __restrict__ x, const __nv_bfloat16* __restrict__ gate_w, __nv_bfloat16* __restrict__ out) {
    extern __shared__ __align__(1024) uint8_t sp[];
    const uint32_t sb = smem_u32(sp);
    if ((sb & 0x3FFFF) != SMEM_BASE) __trap();
    const int tid = threadIdx.x, lane = tid & 31;
    const int warp = __shfl_sync(~0u, tid >> 5, 0), wg = warp >> 2, w4 = warp & 3;
    const int bid = blockIdx.x, rank = bid & 1, qb = (bid >> 1) & 3, head = ((bid >> 3) << 1) | rank;
    const int slot = head * 4 + qb;
    STAMP(0);

    if (tid == 0) {
        asm volatile("prefetch.tensormap [%0];" ::"l"(&tm_x) : "memory");
        asm volatile("prefetch.tensormap [%0];" ::"l"(&tm_wa) : "memory");
        asm volatile("prefetch.tensormap [%0];" ::"l"(&tm_wb) : "memory");
        for (int s = 0; s < NSLOT; s++) { mbar_init(sb + FULL_BAR + 8 * s, 1); mbar_init(sb + EMPTY_BAR + 8 * s, 8); }
        for (int s = 0; s < 8; s++) mbar_init(sb + W_BAR + 8 * s, 1);
        mbar_init(sb + X_BAR, 3);
        asm volatile("fence.mbarrier_init.release.cluster;" ::: "memory");
        STAMPH(0);
        for (int t = 0; t < 4; t++) {
            mbar_expect_tx(sb + FULL_BAR + 8 * t, XS_BYTES);
            tma_2d(sb + t * XS_BYTES, &tm_x, step_kb(t) * 64, qb * 512 + step_half(t) * 256, sb + FULL_BAR + 8 * t);
            if (t < 3) {
                mbar_expect_tx(sb + W_BAR + 8 * t, WS_BYTES);
                tma_4d(sb + WBUF + (7 - t) * WS_BYTES, &tm_wa, 0, t * 64, head, 0, sb + W_BAR + 8 * t);
                tma_4d(sb + WBUF + (7 - t) * WS_BYTES + 6144, &tm_wb, 0, t * 64, head, 0, sb + W_BAR + 8 * t);
            }
        }
        STAMPH(1);
    }
    if (tid >= 32 && tid < 48) {
        if (tid != 37) reinterpret_cast<uint32_t*>(sp + MISC)[tid - 32] = tid == 36 ? 0xbf80bf80u : 0u;
    }
    if (tid >= 64 && tid < 88) reinterpret_cast<float*>(sp + CONSTS)[tid - 64] = ((XMASK >> ((tid - 64) >> 1)) & 1) ? 0.f : EXP_MAGIC;
    __syncthreads();
    asm volatile("barrier.cluster.arrive.relaxed.aligned;" ::: "memory");
    if (tid == 0) STAMPH(2);

    uint32_t qa0[4], qa1[4], qb0[4], qb1[4];
    uint4* const qs = g_qsave + bid * 3584 + tid;
    {
        float acc0[48], acc1[48], nrm[4][4];
        uint32_t kv0[16], kv1[16];
        uint4 gx[2], gw[2];
        uint32_t cnt0;
        const int grow = qb * 512 + head * 16 + warp;
#pragma unroll
        for (int c = 0; c < 2; c++) {
            gx[c] = __ldg(reinterpret_cast<const uint4*>(x + (size_t)grow * DM) + lane + 32 * c);
            gw[c] = __ldg(reinterpret_cast<const uint4*>(gate_w) + lane + 32 * c);
        }
        asm volatile("ld.relaxed.gpu.global.u32 %0, [%1];" : "=r"(cnt0) : "l"(&g_cnt[1][qb * 32]) : "memory");
        const uint32_t ra = sb + KVA + wg * REC + (w4 * 16 + (lane & 15)) * 16 + (lane >> 4) * 1024, rb = ra + (KVB + 4 * REC - KVA);
        const uint64_t da0 = make_desc(SMEM_BASE + wg * 8192, 16, 1024, 1);
        constexpr uint64_t db0 = make_desc(SMEM_BASE + WBUF, 2048, 256, 3);
#pragma unroll
        for (int t = 0; t < NSTEP; t++) {
            const int s = t % NSLOT, hf = step_half(t), kb = step_kb(t);
            if (t == 0 && tid == 160) STAMPH(3);
            if (hf == 0) mbar_wait_warp(sb + W_BAR + 8 * kb, 0);
            if (t == 0 && tid == 160) STAMPH(4);
            mbar_wait_warp(sb + FULL_BAR + 8 * s, (t / NSLOT) & 1);
            const uint64_t da = da0 + (uint64_t)(s * (XS_BYTES >> 4)), db = db0 + (uint64_t)((7 - kb) * (WS_BYTES >> 4));
            wg_fence();
#pragma unroll
            for (int k = 0; k < 4; k++) {
                if (kb == 0 && k == 0) wgmma_ss_n96_tb_zero(hf ? acc1 : acc0, da, db);
                else wgmma_ss_n96_tb(hf ? acc1 : acc0, da + 2 * k, db + 32 * k);
            }
            wg_commit();
            if (t >= 1 && t <= 14) wg_wait<1>();
            if (t >= 1 && t - 1 + NSLOT < NSTEP) {
                const int ps = (t - 1) % NSLOT, nt = t - 1 + NSLOT;
                if (w4 == 3 && lane == 0) mbar_arrive_cluster(sb + EMPTY_BAR + 8 * ps, nt & 1);
                if (tid == 0 && step_half(nt) == 0) {
                    const int nk = step_kb(nt);
                    mbar_expect_tx(sb + W_BAR + 8 * nk, WS_BYTES);
                    tma_4d(sb + WBUF + (7 - nk) * WS_BYTES, &tm_wa, 0, nk * 64, head, 0, sb + W_BAR + 8 * nk);
                    tma_4d(sb + WBUF + (7 - nk) * WS_BYTES + 6144, &tm_wb, 0, nk * 64, head, 0, sb + W_BAR + 8 * nk);
                }
                __syncwarp();
                if (warp == 0 && (nt & 1) == rank) mbar_wait_warp(sb + EMPTY_BAR + 8 * ps, ((t - 1) / NSLOT) & 1);
                if (tid == 0) {
                    mbar_expect_tx(sb + FULL_BAR + 8 * ps, XS_BYTES);
                    if ((nt & 1) == rank)
                        tma_2d_mc(sb + ps * XS_BYTES, &tm_x, step_kb(nt) * 64, qb * 512 + step_half(nt) * 256, sb + FULL_BAR + 8 * ps, 3);
                }
                __syncwarp();
            }
            if (t == 0) STAMP(1);
            if (t == 0) asm volatile("barrier.cluster.wait.aligned;" ::: "memory");
            if (t == 1) {
                float ga = 0.f, gb = 0.f;
#pragma unroll
                for (int c = 0; c < 2; c++) {
                    const uint32_t av[4] = {gx[c].x, gx[c].y, gx[c].z, gx[c].w}, gv[4] = {gw[c].x, gw[c].y, gw[c].z, gw[c].w};
#pragma unroll
                    for (int i = 0; i < 4; i++) {
                        ga += __uint_as_float(av[i] << 16) * __uint_as_float(gv[i] << 16);
                        gb += __uint_as_float(av[i] & 0xffff0000u) * __uint_as_float(gv[i] & 0xffff0000u);
                    }
                }
                gx[0].x = __float_as_uint(ga + gb);
            }
            if (t == 2) {
                float ga = __uint_as_float(gx[0].x);
#pragma unroll
                for (int o = 16; o; o >>= 1) ga += __shfl_xor_sync(~0u, ga, o);
                if (lane == 0) g_gate[grow] = __fdividef(1.f, 1.f + __expf(-ga));
                if (tid == 37) reinterpret_cast<uint32_t*>(sp + MISC)[5] = cnt0;
            }
            if (t >= 4 && t < 8 && tid == 128 * (t - 4) + 32) {
#pragma unroll
                for (int i = 11 * (t - 4); i < 11 * (t - 3) && i < 41; i++) mbar_init(sb + P3BAR + 8 * i, i >= 38 ? 4 : (i >= 30 ? 2 : 1));
            }
            if (t == 13) { fence_regs(acc0); finish_branch(acc0, 1, nrm, 0, qb0, kv0); }
            if (t == 14) {
                qs[2 * 512] = make_uint4(qb0[0], qb0[1], qb0[2], qb0[3]);
                finish_branch(acc0, 0, nrm, 0, qa0, kv0);
            }
            if (t == 15) {
                __syncthreads();
                stmatrix_x4(ra, kv0[0], kv0[1], kv0[2], kv0[3]);
                stmatrix_x4(ra + 2048, kv0[4], kv0[5], kv0[6], kv0[7]);
                stmatrix_x4(rb, kv0[8], kv0[9], kv0[10], kv0[11]);
                stmatrix_x4(rb + 2048, kv0[12], kv0[13], kv0[14], kv0[15]);
                uint8_t* const op = sp + KVA + (tid >> 6) * REC + 4096 + (tid & 63) * 16;
                *reinterpret_cast<uint4*>(op) = make_uint4(0x3f803f80u, 0x3f803f80u, 0x3f803f80u, 0x3f803f80u);
                *reinterpret_cast<uint4*>(op + (KVB + 4 * REC - KVA)) = make_uint4(0x3f803f80u, 0x3f803f80u, 0x3f803f80u, 0x3f803f80u);
            }
        }
        wg_wait<0>();
        fence_regs(acc1);
        STAMP(2);
        finish_branch(acc1, 0, nrm, 1, qa1, kv1);
        finish_branch(acc1, 1, nrm, 1, qb1, kv1);
        stmatrix_x4(ra + 4 * REC, kv1[0], kv1[1], kv1[2], kv1[3]);
        stmatrix_x4(ra + 4 * REC + 2048, kv1[4], kv1[5], kv1[6], kv1[7]);
        stmatrix_x4(rb + 4 * REC, kv1[8], kv1[9], kv1[10], kv1[11]);
        stmatrix_x4(rb + 4 * REC + 2048, kv1[12], kv1[13], kv1[14], kv1[15]);
        row_norm_stats(nrm, lane, sb + STATS);
        {
            const uint32_t va = absmax8(kv0 + 4, kv1 + 4), vb = absmax8(kv0 + 12, kv1 + 12);
            if (lane < 2) asm volatile("red.shared.max.u32 [%0], %1;" ::"r"(sb + STATS + 16 + 4 * lane), "r"(lane ? vb : va) : "memory");
        }
        fence_async_smem();
        __syncthreads();
    }
    if (tid == 384) {
        uint8_t* dst = g_kv + (size_t)slot * 61440;
        bulk_s2g(dst, sb + KVA, 8 * REC);
        bulk_s2g(dst + 8 * REC, sb + KVB + 8 * REC, 4 * REC);
        asm volatile("cp.async.bulk.commit_group;" ::: "memory");
    }
    __syncwarp();
    STAMP(3);

    const uint32_t one2 = *reinterpret_cast<volatile uint32_t*>(sp + MISC + 16);
    const uint32_t caddr = sb + CONSTS;
    const float* st = reinterpret_cast<const float*>(sp + STATS);
    __nv_bfloat16* const obase = g_ocat + (size_t)(qb * 512 + wg * 64 + w4 * 16 + (lane >> 2)) * 1024 + head * 16 + 2 * (lane & 3);
    Scores S;
    float O[12];
    auto load_q = [&](uint32_t (&q)[4], int job) {
        asm volatile("ld.global.v4.u32 {%0, %1, %2, %3}, [%4];" : "=r"(q[0]), "=r"(q[1]), "=r"(q[2]), "=r"(q[3]) : "l"(qs + job * 512) : "memory");
    };
    const uint32_t* const stu = reinterpret_cast<const uint32_t*>(sp + STATS);
    auto cnt_target = [&]() { return *reinterpret_cast<const uint32_t*>(sp + MISC + 20) + 32u; };
    const int rowE = qb * 512 + 256 + (head >> 3) * 64, rowL = rowE - 256, n0 = (head & 7) * 64;
    auto p3_load_w = [&](int g) {
        mbar_expect_tx(sb + P3BAR + 8 * g, 32768);
        tma_2d(sb + (g == 0 ? 0 : g == 3 ? 4 : 16 + 4 * g) * 8192, g < 2 ? &tm_wob4 : &tm_woa4, n0, (g & 1) * 256, sb + P3BAR + 8 * g);
    };
    auto p3_load_o = [&](int late) {
        mbar_expect_tx(sb + P3BAR + 8 * (4 + late), 32768);
        tma_3d(sb + (8 + 4 * late) * 8192, &tm_o4, 0, late ? rowL : rowE, 8, sb + P3BAR + 8 * (4 + late));
    };
    auto save_q = [&](const uint32_t (&q)[4], int job) { qs[job * 512] = make_uint4(q[0], q[1], q[2], q[3]); };
#pragma unroll
    for (int i = 0; i < 8; i++) S.m[i] = 0.f;
#pragma unroll
    for (int i = 0; i < 6; i++) load_magic(S, i, caddr);
    zero_o(O);
    fence_regs(S.m); fence_regs(S.p);
    wg_fence();
    issue_qk(S, qb1, dKB + (wg + 4) * RECD);
    wg_commit();
    const bool fast = shift_free_ok(st[0], st[1], st[4], st[4]) & shift_free_ok(st[2], st[3], st[5], st[5]);
    uint32_t redo = fast ? 0 : 15;
    wg_wait<0>();
    fence_regs(S.m); fence_regs(S.p);
    {
        const uint32_t kd = dKB + (wg + 4) * RECD, vd = dVB + (wg + 4) * RECD;
        if (fast) {
            attn_step<2, true>(S, O, qb1, kd + RECD, vd, one2, caddr);
            attn_run<1>(S, O, qb1, vd + RECD, 3, one2, caddr);
        }
        if (tid == 384) {
            const unsigned long long fv = ((unsigned long long)((cnt_target() << 11) | up16(max(stu[4], stu[5]))) << 32) | (up16(stu[3]) << 16) | up16(stu[1]);
            asm volatile("cp.async.bulk.wait_group 0;" ::: "memory");
            asm volatile("st.relaxed.gpu.global.u64 [%0], %1;" ::"l"(g_flag + slot), "l"(fv) : "memory");
            STAMPH(9);
        }
        __syncwarp();
        save_q(qb1, 3);
        if (fast) {
            attn_step<1, true>(S, O, qa0, dKA, vd + 4 * RECD, one2, caddr);
            store_o(O, obase + 256 * 1024 + 512);
        }
    }
    STAMP(4);
    {
        const int os = head * 4 + ((qb + wg + 1) & 3);
        const bool fetcher = w4 == 0 && wg < 3;
        auto poll = [&]() -> unsigned long long {
            unsigned long long f;
            asm volatile("ld.relaxed.gpu.global.u64 %0, [%1];" : "=l"(f) : "l"(g_flag + os) : "memory");
            return f;
        };
        if (fast) {
            zero_o(O);
            attn_step<0, true>(S, O, qa0, dKA + RECD, dVA, one2, caddr);
            attn_step<0, true>(S, O, qa0, dKA + 2 * RECD, dVA + RECD, one2, caddr);
        }
        unsigned long long f = 0;
        if (fetcher) f = poll();
        if (fast) {
            attn_step<0, true>(S, O, qa0, dKA + 3 * RECD, dVA + 2 * RECD, one2, caddr);
            attn_step<0, true>(S, O, qa0, dKA + 4 * RECD, dVA + 3 * RECD, one2, caddr);
        }
        if (fetcher) {
            const uint32_t tag = (cnt_target() >> 5) & 0xffffu;
#pragma unroll 1
            for (uint32_t i = 0; !__all_sync(~0u, (uint32_t)(f >> 48) == tag); i++) {
                if (i == (1u << 22)) __trap();
                f = poll();
            }
        }
        if (fetcher && lane == 0) {
            asm volatile("fence.acquire.gpu;" ::: "memory");
            asm volatile("fence.proxy.async.global;" ::: "memory");
            const bool halo = wg == 2 && qb > 0;
            *reinterpret_cast<unsigned long long*>(sp + STATS + 32 + wg * 8) = f;
            mbar_expect_tx(sb + X_BAR, halo ? 12 * REC : 8 * REC);
            const uint8_t* src = g_kv + (size_t)os * 61440;
            bulk_g2s(sb + KVA + (wg + 1) * 8 * REC, src, 8 * REC, sb + X_BAR);
            if (halo) bulk_g2s(sb + KVB, src + 8 * REC, 4 * REC, sb + X_BAR);
            if (wg == 1) STAMPH(10);
        }
        __syncwarp();
        if (fast) {
            attn_step<0, true>(S, O, qa0, dKA + 5 * RECD, dVA + 4 * RECD, one2, caddr);
            attn_step<0, true>(S, O, qa0, dKA + 6 * RECD, dVA + 5 * RECD, one2, caddr);
        }
        if (fast) {
            attn_step<0, true>(S, O, qa0, dKA + 7 * RECD, dVA + 6 * RECD, one2, caddr);
            attn_step<0, true>(S, O, qa1, dKA, dVA + 7 * RECD, one2, caddr);
#pragma unroll
            for (int i = 0; i < 3; i++)
                qs[(4 + i) * 512] = make_uint4(__float_as_uint(O[4 * i]), __float_as_uint(O[4 * i + 1]), __float_as_uint(O[4 * i + 2]), __float_as_uint(O[4 * i + 3]));
        }
    }
    save_q(qa0, 0);
    STAMP(11);
    const int first = qb > 0 ? 0 : 4 - wg;
    {
        if (fast) {
            zero_o(O);
            attn_run<AUNR>(S, O, qa1, dVA, 6, one2, caddr);
        }
        mbar_wait_warp(sb + X_BAR, 0);
        STAMP(12);
        save_q(qa1, 1);
        {
            const uint32_t ka = max(stu[1], max(stu[8] << 16, max(stu[10] << 16, stu[12] << 16)));
            const uint32_t va = max(stu[4], max(stu[9] << 16, max(stu[11] << 16, stu[13] << 16)));
            if (!shift_free_ok(st[0], __uint_as_float(ka), st[4], __uint_as_float(va))) redo |= 3;
            if (!shift_free_ok(st[2], __uint_as_float(max(stu[3], stu[12] & 0xffff0000u)), st[5], __uint_as_float(max(stu[5], stu[13] << 16)))) redo |= 4;
        }
        if (fast) {
            attn_run<AUNR>(S, O, qa1, dVA + 6 * RECD, 24, one2, caddr);
            load_q(qb0, 2);
            attn_step<0, true>(S, O, qa1, dKA + 31 * RECD, dVA + 30 * RECD, one2, caddr);
            attn_step<0, true>(S, O, qb0, dKB + (wg + first) * RECD, dVA + 31 * RECD, one2, caddr);
            store_o(O, obase + 256 * 1024);
        }
    }
    STAMP(5);
    if (fast) {
        uint32_t vd = dVB + (wg + first) * RECD;
        zero_o(O);
        if (qb > 0) { attn_step<2, true>(S, O, qb0, vd + RECD + (dKA - dVA), vd, one2, caddr); vd += RECD; }
        load_q(qa0, 0);
        attn_run<1>(S, O, qb0, vd, qb > 0 ? 3 : wg, one2, caddr);
        attn_step<1, true>(S, O, qa0, dKA + 8 * RECD, dVB + (wg + 4) * RECD, one2, caddr);
        store_o(O, obase + 512);
    }
    STAMP(6);
    const bool pf = !redo;
    if (pf) asm volatile("bar.arrive 7, 544;" ::: "memory");
    auto checkpoint = [&](int i) { if (pf && w4 == 3 && lane == 0) mbar_arrive(sb + CP_BAR + 8 * i); };
    STAMP(8);
    if (fast) {
#pragma unroll
        for (int i = 0; i < 3; i++)
            asm volatile("ld.global.v4.f32 {%0, %1, %2, %3}, [%4];" : "=f"(O[4 * i]), "=f"(O[4 * i + 1]), "=f"(O[4 * i + 2]), "=f"(O[4 * i + 3]) : "l"(qs + (4 + i) * 512) : "memory");
        attn_run<AUNR>(S, O, qa0, dVA + 8 * RECD, 6, one2, caddr);
        checkpoint(0);
        if (pf && warp == 15) {
            asm volatile("bar.sync 7, 544;" ::: "memory");
            if (lane == 0) cnt_release(&g_cnt[0][qb * 32], 1);
            __syncwarp();
        }
        STAMP(9);
        attn_run<AUNR>(S, O, qa0, dVA + 14 * RECD, 8, one2, caddr);
        if (pf && warp == 11) {
            mbar_wait_warp(sb + CP_BAR, 0);
            if (lane == 0) { p3_load_w(0); p3_load_w(1); p3_load_w(2); p3_load_w(3); }
            __syncwarp();
        }
        if (pf && warp == 7) cnt_wait_warp(&g_cnt[0][qb * 32], cnt_target());
        checkpoint(1);
        STAMP(10);
        attn_run<AUNR>(S, O, qa0, dVA + 22 * RECD, 6, one2, caddr);
        checkpoint(2);
        if (pf && warp == 11) {
            mbar_wait_warp(sb + CP_BAR + 8, 0);
            if (lane == 0) { asm volatile("fence.proxy.async.global;" ::: "memory"); p3_load_o(0); }
            __syncwarp();
        }
        STAMP(13);
        attn_step<0, true>(S, O, qa0, dKA + 29 * RECD, dVA + 28 * RECD, one2, caddr);
        attn_step<0, true>(S, O, qa0, dKA + 30 * RECD, dVA + 29 * RECD, one2, caddr);
        if (pf && warp == 15) {
            mbar_wait_warp(sb + CP_BAR + 16, 0);
            if (lane == 0) { asm volatile("fence.proxy.async.global;" ::: "memory"); p3_load_o(1); }
            __syncwarp();
        }
        STAMP(14);
        attn_step<0, true>(S, O, qa0, dKA + 31 * RECD, dVA + 30 * RECD, one2, caddr);
        attn_step<0, false>(S, O, qa0, 0, dVA + 31 * RECD, one2, caddr);
        store_o(O, obase);
    }
    STAMP(7);
#pragma unroll 1
    for (int job = 0; redo >> job; job++) {
        if (!((redo >> job) & 1)) continue;
        const uint4 qv = qs[job * 512];
        const uint32_t q[4] = {qv.x, qv.y, qv.z, qv.w};
        const int f0 = job == 2 ? first : 0;
        const uint32_t off = (wg + (job & 1) * 4 + f0) * RECD;
        const bool isb = job >= 2;
        attn_slow(O, q, isb ? dKB + off : dKA, isb ? dVB + off : dVA, isb ? 5 - f0 : 32, isb && f0 == 0, isb);
        store_o(O, obase + (job & 1) * 256 * 1024 + (isb ? 512 : 0));
    }
    __syncthreads();
    STAMP2(0);

    if (wg >= 2) {
        if (warp == 12) {
            if (lane == 0) {
                if (redo) cnt_release(&g_cnt[0][qb * 32], 1);
                cnt_release(&g_cnt[1][qb * 32], 1);
            }
            __syncwarp();
            cnt_wait_warp(&g_cnt[1][qb * 32], cnt_target());
            STAMP2(1);
            if (lane == 0) {
                asm volatile("fence.proxy.async.global;" ::: "memory");
#pragma unroll 1
                for (int i = 0; i < 8; i++) {
                    mbar_wait(sb + P3BAR + 8 * (30 + i), 0);
                    mbar_expect_tx(sb + P3BAR + 8 * (22 + i), 8192);
                    tma_2d(sb + (i < 4 ? 12 + i : i - 4) * 8192, &tm_o1, i * 64, rowL, sb + P3BAR + 8 * (22 + i));
                }
            }
        }
        if (warp == 8) {
            if (redo) {
                if (lane == 0) { p3_load_w(0); p3_load_w(1); p3_load_w(2); p3_load_w(3); }
                __syncwarp();
                cnt_wait_warp(&g_cnt[0][qb * 32], cnt_target());
            }
            if (lane == 0) {
                asm volatile("fence.proxy.async.global;" ::: "memory");
                if (redo) { p3_load_o(0); p3_load_o(1); }
#pragma unroll 1
                for (int i = 0; i < 4; i++) {
                    mbar_expect_tx(sb + P3BAR + 8 * (6 + i), 8192);
                    tma_2d(sb + (16 + i) * 8192, &tm_o1, (12 + i) * 64, rowE, sb + P3BAR + 8 * (6 + i));
                }
#pragma unroll 1
                for (int i = 0; i < 8; i++) {
                    mbar_wait(sb + P3BAR + 8 * (30 + i), 0);
                    if (i < 4) {
                        mbar_expect_tx(sb + P3BAR + 8 * (10 + i), 8192);
                        tma_2d(sb + i * 8192, &tm_o1, (12 + i) * 64, rowL, sb + P3BAR + 8 * (10 + i));
                    }
                    mbar_expect_tx(sb + P3BAR + 8 * (14 + i), 8192);
                    tma_2d(sb + (i < 4 ? 8 + i : 12 + i) * 8192, &tm_o1, i * 64, rowE, sb + P3BAR + 8 * (14 + i));
                }
            }
        }
        return;
    }
    {
        float accA[32], accB[32];
#pragma unroll
        for (int i = 0; i < 32; i++) { accA[i] = 0.f; accB[i] = 0.f; }
        fence_regs(accA); fence_regs(accB);
        constexpr uint64_t da0 = make_desc(SMEM_BASE, 16, 1024, 1);
        constexpr uint64_t db0 = make_desc(SMEM_BASE, 8192, 1024, 1);
        const int row = (wg ? rowL : rowE) + w4 * 16;
        float g0 = 0.f, g1 = 0.f;
#pragma unroll
        for (int kb = 0; kb < 16; kb++) {
            const int j = kb & 7;
            const int wslot = kb < 4 ? kb : (kb < 12 ? 16 + kb : kb - 8);
            const int oslot = wg ? (j < 4 ? 12 + j : j - 4) : (j < 4 ? 8 + j : 12 + j);
            if ((kb & 3) == 0) mbar_wait_warp(sb + P3BAR + 8 * (kb >> 2), 0);
            if (kb >= 8) mbar_wait_warp(sb + P3BAR + 8 * (14 + j) + wg * 64, 0);
            else if (kb == 0) mbar_wait_warp(sb + P3BAR + 8 * (4 + wg), 0);
            else if (kb >= 4) mbar_wait_warp(sb + P3BAR + 8 * (2 + kb) + wg * 32, 0);
            if (kb == 0) {
                asm volatile("ld.relaxed.gpu.global.f32 %0, [%1];" : "=f"(g0) : "l"(g_gate + row + (lane >> 2)) : "memory");
                asm volatile("ld.relaxed.gpu.global.f32 %0, [%1];" : "=f"(g1) : "l"(g_gate + row + (lane >> 2) + 8) : "memory");
            }
            const uint64_t da = da0 + (uint64_t)(oslot * 512), db = db0 + (uint64_t)(wslot * 512);
            wg_fence();
#pragma unroll
            for (int k = 0; k < 4; k++) {
                if (kb < 8) wgmma_ss_n64_tb(accB, da + 2 * k, db + 128 * k);
                else wgmma_ss_n64_tb(accA, da + 2 * k, db + 128 * k);
            }
            wg_commit();
            if (kb == 7) wg_wait<0>(); else if (kb >= 1 && kb < 7) wg_wait<1>();
            if (kb >= 1 && kb < 8) {
                if (w4 == 0 && lane == 0) {
                    mbar_arrive(sb + P3BAR + 8 * (30 + kb - 1));
                    if (kb == 7) mbar_arrive(sb + P3BAR + 8 * 37);
                }
                __syncwarp();
            }
        }
        wg_wait<0>();
        fence_regs(accA); fence_regs(accB);
        STAMP2(2);
        const uint32_t toff = (8 + wg * 4) * 8192 + w4 * 2048;
        const int mrow = (lane & 7) + ((lane >> 3) & 1) * 8;
#pragma unroll
        for (int p = 0; p < 4; p++) {
            uint32_t r[4];
#pragma unroll
            for (int h = 0; h < 2; h++) {
                const int i = (2 * p + h) * 4;
                r[2 * h] = pack_bf16(g0 * accA[i] + (1.f - g0) * accB[i], g0 * accA[i + 1] + (1.f - g0) * accB[i + 1]);
                r[2 * h + 1] = pack_bf16(g1 * accA[i + 2] + (1.f - g1) * accB[i + 2], g1 * accA[i + 3] + (1.f - g1) * accB[i + 3]);
            }
            const int chunk = 2 * p + (lane >> 4);
            stmatrix_x4(sb + toff + mrow * 128 + ((chunk ^ (mrow & 7)) << 4), r[0], r[1], r[2], r[3]);
        }
        __syncwarp();
#pragma unroll
        for (int p = 0; p < 4; p++) {
            const int r = p * 4 + (lane >> 3), c = lane & 7;
            const uint4 v = *reinterpret_cast<const uint4*>(sp + toff + r * 128 + ((c ^ (r & 7)) << 4));
            *reinterpret_cast<uint4*>(out + (size_t)(row + r) * DM + n0 + c * 8) = v;
        }
        STAMP2(3);
    }
}

typedef CUresult (*EncodeFn)(CUtensorMap*, CUtensorMapDataType, cuuint32_t, void*, const cuuint64_t*, const cuuint64_t*,
                             const cuuint32_t*, const cuuint32_t*, CUtensorMapInterleave, CUtensorMapSwizzle,
                             CUtensorMapL2promotion, CUtensorMapFloatOOBfill);

void encode(EncodeFn fn, CUtensorMap* tm, const void* ptr, int rank, const cuuint64_t* dims, const cuuint64_t* strides,
            const cuuint32_t* box, CUtensorMapSwizzle swz) {
    const cuuint32_t es[4] = {1, 1, 1, 1};
    fn(tm, CU_TENSOR_MAP_DATA_TYPE_BFLOAT16, rank, const_cast<void*>(ptr), dims, strides, box, es, CU_TENSOR_MAP_INTERLEAVE_NONE,
       swz, CU_TENSOR_MAP_L2_PROMOTION_L2_256B, CU_TENSOR_MAP_FLOAT_OOB_FILL_NONE);
}

}

extern "C" void kernel_launch(void* const* d_in, const int* in_sizes, int n_in, void* d_out, int out_size) {
    (void)in_sizes; (void)n_in; (void)out_size;
    const __nv_bfloat16* x = (const __nv_bfloat16*)d_in[0];
    const __nv_bfloat16* gate_w = (const __nv_bfloat16*)d_in[6];
    static EncodeFn fn = nullptr;
    static void* ocat = nullptr;
    if (!fn) {
        cudaDriverEntryPointQueryResult qr;
        cudaGetDriverEntryPoint("cuTensorMapEncodeTiled", (void**)&fn, cudaEnableDefault, &qr);
        cudaGetSymbolAddress(&ocat, g_ocat);
        cudaFuncSetAttribute(fused_kernel, cudaFuncAttributeMaxDynamicSharedMemorySize, SMEM1_BYTES);
    }
    CUtensorMap tm_x, tm_wa, tm_wb, tm_woa4, tm_wob4, tm_o1, tm_o4;
    {
        const cuuint64_t dims[2] = {512, 2048}, str[1] = {1024};
        const cuuint32_t box[2] = {64, 256};
        encode(fn, &tm_x, x, 2, dims, str, box, CU_TENSOR_MAP_SWIZZLE_128B);
    }
    {
        const cuuint64_t dims[4] = {16, 512, 32, 3}, str[3] = {3072, 32, 1024};
        const cuuint32_t box[4] = {16, 64, 1, 3};
        encode(fn, &tm_wa, d_in[1], 4, dims, str, box, CU_TENSOR_MAP_SWIZZLE_32B);
        encode(fn, &tm_wb, d_in[4], 4, dims, str, box, CU_TENSOR_MAP_SWIZZLE_32B);
    }
    {
        const cuuint64_t dims[2] = {1024, 2048}, str[1] = {2048};
        const cuuint32_t box[2] = {64, 64};
        encode(fn, &tm_o1, ocat, 2, dims, str, box, CU_TENSOR_MAP_SWIZZLE_128B);
        const cuuint64_t dims3[3] = {64, 2048, 16}, str3[2] = {2048, 128};
        const cuuint32_t box3[3] = {64, 64, 4};
        encode(fn, &tm_o4, ocat, 3, dims3, str3, box3, CU_TENSOR_MAP_SWIZZLE_128B);
    }
    {
        const cuuint64_t dims[2] = {512, 512}, str[1] = {1024};
        const cuuint32_t box4[2] = {64, 256};
        encode(fn, &tm_woa4, d_in[2], 2, dims, str, box4, CU_TENSOR_MAP_SWIZZLE_128B);
        encode(fn, &tm_wob4, d_in[5], 2, dims, str, box4, CU_TENSOR_MAP_SWIZZLE_128B);
    }
    cudaLaunchAttribute at[1];
    at[0].id = cudaLaunchAttributeClusterDimension;
    at[0].val.clusterDim.x = 2; at[0].val.clusterDim.y = 1; at[0].val.clusterDim.z = 1;
    cudaLaunchConfig_t cfg = {};
    cfg.gridDim = dim3(128); cfg.blockDim = dim3(512); cfg.dynamicSmemBytes = SMEM1_BYTES;
    cfg.stream = cudaStreamPerThread; cfg.attrs = at; cfg.numAttrs = 1;
    cudaLaunchKernelEx(&cfg, fused_kernel, tm_x, tm_wa, tm_wb, tm_woa4, tm_wob4, tm_o1, tm_o4, x, gate_w, (__nv_bfloat16*)d_out);
}
```

```cpp
#include <cuda_runtime.h>
#include <cuda_bf16.h>
#include <cuda.h>
#include <stdint.h>

namespace {

constexpr int SEQ = 2048, DM = 512;

__device__ __align__(1024) uint8_t g_kv[128 * 61440];
__device__ unsigned long long g_flag[128];
__device__ uint32_t g_cnt[2][4 * 32];
__device__ uint4 g_qsave[128 * 7 * 512];
__device__ float g_gate[SEQ];
__device__ __align__(1024) __nv_bfloat16 g_ocat[SEQ * 1024];

__device__ __forceinline__ uint32_t smem_u32(const void* p) { return (uint32_t)__cvta_generic_to_shared(p); }
__device__ __forceinline__ void wg_fence() { asm volatile("wgmma.fence.sync.aligned;" ::: "memory"); }
__device__ __forceinline__ void wg_commit() { asm volatile("wgmma.commit_group.sync.aligned;" ::: "memory"); }
template <int N> __device__ __forceinline__ void wg_wait() { asm volatile("wgmma.wait_group.sync.aligned %0;" ::"n"(N) : "memory"); }
constexpr uint32_t SMEM_BASE = 1024;
__host__ __device__ constexpr uint64_t make_desc(uint32_t addr, uint32_t lbo, uint32_t sbo, uint32_t mode) {
    return (uint64_t)((addr & 0x3FFFF) >> 4) | ((uint64_t)(lbo >> 4) << 16) | ((uint64_t)(sbo >> 4) << 32) | ((uint64_t)mode << 62);
}
template <int N> __device__ __forceinline__ void fence_regs(float (&r)[N]) {
#pragma unroll
    for (int i = 0; i < N; i++) asm volatile("" : "+f"(r[i])::"memory");
}
template <int N> __device__ __forceinline__ void fence_regs(uint32_t (&r)[N]) {
#pragma unroll
    for (int i = 0; i < N; i++) asm volatile("" : "+r"(r[i])::"memory");
}
__device__ __forceinline__ void mbar_init(uint32_t bar, uint32_t count) {
    asm volatile("mbarrier.init.shared::cta.b64 [%0], %1;" ::"r"(bar), "r"(count) : "memory");
}
__device__ __forceinline__ void mbar_expect_tx(uint32_t bar, uint32_t bytes) {
    asm volatile("mbarrier.arrive.expect_tx.shared::cta.b64 _, [%0], %1;" ::"r"(bar), "r"(bytes) : "memory");
}
__device__ __forceinline__ void mbar_arrive_cluster(uint32_t bar, uint32_t cta) {
    asm volatile("{\n.reg .b32 ra;\nmapa.shared::cluster.u32 ra, %0, %1;\n"
                 "mbarrier.arrive.shared::cluster.b64 _, [ra];\n}\n" ::"r"(bar), "r"(cta) : "memory");
}
__device__ __forceinline__ bool mbar_try(uint32_t bar, uint32_t parity) {
    uint32_t ok;
    asm volatile("{\n.reg .pred p;\nmbarrier.try_wait.parity.shared::cta.b64 p, [%1], %2;\nselp.u32 %0, 1, 0, p;\n}\n"
                 : "=r"(ok) : "r"(bar), "r"(parity) : "memory");
    return ok != 0;
}
__device__ __forceinline__ void mbar_wait(uint32_t bar, uint32_t parity) {
    if (mbar_try(bar, parity)) return;
#pragma unroll 1
    for (uint32_t i = 0; i < (1u << 22); i++)
        if (mbar_try(bar, parity)) return;
    __trap();
}
__device__ __forceinline__ void mbar_wait_warp(uint32_t bar, uint32_t parity) {
    if (__all_sync(~0u, mbar_try(bar, parity))) return;
#pragma unroll 1
    for (uint32_t i = 0; i < (1u << 22); i++)
        if (__all_sync(~0u, mbar_try(bar, parity))) return;
    __trap();
}
__device__ __forceinline__ void fence_async_smem() { asm volatile("fence.proxy.async.shared::cta;" ::: "memory"); }
__device__ __forceinline__ void tma_2d(uint32_t dst, const CUtensorMap* tm, int c0, int c1, uint32_t bar) {
    asm volatile("cp.async.bulk.tensor.2d.shared::cluster.global.mbarrier::complete_tx::bytes [%0], [%1, {%3, %4}], [%2];"
                 ::"r"(dst), "l"(tm), "r"(bar), "r"(c0), "r"(c1) : "memory");
}
__device__ __forceinline__ void tma_2d_mc(uint32_t dst, const CUtensorMap* tm, int c0, int c1, uint32_t bar, uint16_t mask) {
    asm volatile("cp.async.bulk.tensor.2d.shared::cluster.global.mbarrier::complete_tx::bytes.multicast::cluster [%0], [%1, {%3, %4}], [%2], %5;"
                 ::"r"(dst), "l"(tm), "r"(bar), "r"(c0), "r"(c1), "h"(mask) : "memory");
}
__device__ __forceinline__ void tma_3d(uint32_t dst, const CUtensorMap* tm, int c0, int c1, int c2, uint32_t bar) {
    asm volatile("cp.async.bulk.tensor.3d.shared::cluster.global.mbarrier::complete_tx::bytes [%0], [%1, {%3, %4, %5}], [%2];"
                 ::"r"(dst), "l"(tm), "r"(bar), "r"(c0), "r"(c1), "r"(c2) : "memory");
}
__device__ __forceinline__ void mbar_arrive(uint32_t bar) {
    asm volatile("mbarrier.arrive.shared::cta.b64 _, [%0];" ::"r"(bar) : "memory");
}
__device__ __forceinline__ void tma_4d(uint32_t dst, const CUtensorMap* tm, int c0, int c1, int c2, int c3, uint32_t bar) {
    asm volatile("cp.async.bulk.tensor.4d.shared::cluster.global.mbarrier::complete_tx::bytes [%0], [%1, {%3, %4, %5, %6}], [%2];"
                 ::"r"(dst), "l"(tm), "r"(bar), "r"(c0), "r"(c1), "r"(c2), "r"(c3) : "memory");
}
__device__ __forceinline__ void bulk_g2s(uint32_t dst, const void* src, uint32_t bytes, uint32_t bar) {
    asm volatile("cp.async.bulk.shared::cluster.global.mbarrier::complete_tx::bytes [%0], [%1], %2, [%3];"
                 ::"r"(dst), "l"(src), "r"(bytes), "r"(bar) : "memory");
}
__device__ __forceinline__ void bulk_s2g(void* dst, uint32_t src, uint32_t bytes) {
    asm volatile("cp.async.bulk.global.shared::cta.bulk_group [%0], [%1], %2;" ::"l"(dst), "r"(src), "r"(bytes) : "memory");
}
__device__ __forceinline__ void stmatrix_x4(uint32_t addr, uint32_t r0, uint32_t r1, uint32_t r2, uint32_t r3) {
    asm volatile("stmatrix.sync.aligned.m8n8.x4.shared.b16 [%0], {%1, %2, %3, %4};" ::"r"(addr), "r"(r0), "r"(r1), "r"(r2), "r"(r3) : "memory");
}
__device__ __forceinline__ float ex2(float x) { float y; asm("ex2.approx.ftz.f32 %0, %1;" : "=f"(y) : "f"(x)); return y; }
__device__ __forceinline__ uint32_t pack_bf16(float lo, float hi) {
    uint32_t r; asm("cvt.rn.bf16x2.f32 %0, %1, %2;" : "=r"(r) : "f"(hi), "f"(lo)); return r;
}

__device__ __forceinline__ void wgmma_ss_n96_tb(float (&d)[48], uint64_t da, uint64_t db) {
    asm volatile("wgmma.mma_async.sync.aligned.m64n96k16.f32.bf16.bf16 {"
        "%0, %1, %2, %3, %4, %5, %6, %7, %8, %9, %10, %11, %12, %13, %14, %15 "
        "%16, %17, %18, %19, %20, %21, %22, %23, %24, %25, %26, %27, %28, %29, %30, %31 "
        "%32, %33, %34, %35, %36, %37, %38, %39, %40, %41, %42, %43, %44, %45, %46, %47}, "
        "%48, %49, 1, 1, 1, 0, 1;\n"
        : "+f"(d[0]), "+f"(d[1]), "+f"(d[2]), "+f"(d[3]), "+f"(d[4]), "+f"(d[5]), "+f"(d[6]), "+f"(d[7]),
          "+f"(d[8]), "+f"(d[9]), "+f"(d[10]), "+f"(d[11]), "+f"(d[12]), "+f"(d[13]), "+f"(d[14]), "+f"(d[15]),
          "+f"(d[16]), "+f"(d[17]), "+f"(d[18]), "+f"(d[19]), "+f"(d[20]), "+f"(d[21]), "+f"(d[22]), "+f"(d[23]),
          "+f"(d[24]), "+f"(d[25]), "+f"(d[26]), "+f"(d[27]), "+f"(d[28]), "+f"(d[29]), "+f"(d[30]), "+f"(d[31]),
          "+f"(d[32]), "+f"(d[33]), "+f"(d[34]), "+f"(d[35]), "+f"(d[36]), "+f"(d[37]), "+f"(d[38]), "+f"(d[39]),
          "+f"(d[40]), "+f"(d[41]), "+f"(d[42]), "+f"(d[43]), "+f"(d[44]), "+f"(d[45]), "+f"(d[46]), "+f"(d[47])
        : "l"(da), "l"(db));
}
__device__ __forceinline__ void wgmma_ss_n96_tb_zero(float (&d)[48], uint64_t da, uint64_t db) {
    asm volatile("wgmma.mma_async.sync.aligned.m64n96k16.f32.bf16.bf16 {"
        "%0, %1, %2, %3, %4, %5, %6, %7, %8, %9, %10, %11, %12, %13, %14, %15 "
        "%16, %17, %18, %19, %20, %21, %22, %23, %24, %25, %26, %27, %28, %29, %30, %31 "
        "%32, %33, %34, %35, %36, %37, %38, %39, %40, %41, %42, %43, %44, %45, %46, %47}, "
        "%48, %49, 0, 1, 1, 0, 1;\n"
        : "=f"(d[0]), "=f"(d[1]), "=f"(d[2]), "=f"(d[3]), "=f"(d[4]), "=f"(d[5]), "=f"(d[6]), "=f"(d[7]),
          "=f"(d[8]), "=f"(d[9]), "=f"(d[10]), "=f"(d[11]), "=f"(d[12]), "=f"(d[13]), "=f"(d[14]), "=f"(d[15]),
          "=f"(d[16]), "=f"(d[17]), "=f"(d[18]), "=f"(d[19]), "=f"(d[20]), "=f"(d[21]), "=f"(d[22]), "=f"(d[23]),
          "=f"(d[24]), "=f"(d[25]), "=f"(d[26]), "=f"(d[27]), "=f"(d[28]), "=f"(d[29]), "=f"(d[30]), "=f"(d[31]),
          "=f"(d[32]), "=f"(d[33]), "=f"(d[34]), "=f"(d[35]), "=f"(d[36]), "=f"(d[37]), "=f"(d[38]), "=f"(d[39]),
          "=f"(d[40]), "=f"(d[41]), "=f"(d[42]), "=f"(d[43]), "=f"(d[44]), "=f"(d[45]), "=f"(d[46]), "=f"(d[47])
        : "l"(da), "l"(db));
}
__device__ __forceinline__ void wgmma_ss_n64_tb(float (&d)[32], uint64_t da, uint64_t db) {
    asm volatile("wgmma.mma_async.sync.aligned.m64n64k16.f32.bf16.bf16 {"
        "%0, %1, %2, %3, %4, %5, %6, %7, %8, %9, %10, %11, %12, %13, %14, %15 "
        "%16, %17, %18, %19, %20, %21, %22, %23, %24, %25, %26, %27, %28, %29, %30, %31}, "
        "%32, %33, 1, 1, 1, 0, 1;\n"
        : "+f"(d[0]), "+f"(d[1]), "+f"(d[2]), "+f"(d[3]), "+f"(d[4]), "+f"(d[5]), "+f"(d[6]), "+f"(d[7]),
          "+f"(d[8]), "+f"(d[9]), "+f"(d[10]), "+f"(d[11]), "+f"(d[12]), "+f"(d[13]), "+f"(d[14]), "+f"(d[15]),
          "+f"(d[16]), "+f"(d[17]), "+f"(d[18]), "+f"(d[19]), "+f"(d[20]), "+f"(d[21]), "+f"(d[22]), "+f"(d[23]),
          "+f"(d[24]), "+f"(d[25]), "+f"(d[26]), "+f"(d[27]), "+f"(d[28]), "+f"(d[29]), "+f"(d[30]), "+f"(d[31])
        : "l"(da), "l"(db));
}
template <uint32_t HI>
__device__ __forceinline__ void wgmma_rs_n64_zero(float (&d)[32], uint32_t a0, uint32_t a1, uint32_t a2, uint32_t a3, uint32_t db_lo) {
    asm volatile("{\n.reg .b64 dsc;\nmov.b64 dsc, {%36, %37};\n"
        "wgmma.mma_async.sync.aligned.m64n64k16.f32.bf16.bf16 {"
        "%0, %1, %2, %3, %4, %5, %6, %7, %8, %9, %10, %11, %12, %13, %14, %15 "
        "%16, %17, %18, %19, %20, %21, %22, %23, %24, %25, %26, %27, %28, %29, %30, %31}, "
        "{%32, %33, %34, %35}, dsc, 0, 1, 1, 0;\n}\n"
        : "+f"(d[0]), "+f"(d[1]), "+f"(d[2]), "+f"(d[3]), "+f"(d[4]), "+f"(d[5]), "+f"(d[6]), "+f"(d[7]),
          "+f"(d[8]), "+f"(d[9]), "+f"(d[10]), "+f"(d[11]), "+f"(d[12]), "+f"(d[13]), "+f"(d[14]), "+f"(d[15]),
          "+f"(d[16]), "+f"(d[17]), "+f"(d[18]), "+f"(d[19]), "+f"(d[20]), "+f"(d[21]), "+f"(d[22]), "+f"(d[23]),
          "+f"(d[24]), "+f"(d[25]), "+f"(d[26]), "+f"(d[27]), "+f"(d[28]), "+f"(d[29]), "+f"(d[30]), "+f"(d[31])
        : "r"(a0), "r"(a1), "r"(a2), "r"(a3), "r"(db_lo), "n"(HI));
}
__device__ __forceinline__ void wgmma_rs_n24_tb64(float (&d)[12], uint32_t a0, uint32_t a1, uint32_t a2, uint32_t a3, uint64_t db) {
    asm volatile("wgmma.mma_async.sync.aligned.m64n24k16.f32.bf16.bf16 {"
        "%0, %1, %2, %3, %4, %5, %6, %7, %8, %9, %10, %11}, "
        "{%12, %13, %14, %15}, %16, 1, 1, 1, 1;\n"
        : "+f"(d[0]), "+f"(d[1]), "+f"(d[2]), "+f"(d[3]), "+f"(d[4]), "+f"(d[5]), "+f"(d[6]), "+f"(d[7]),
          "+f"(d[8]), "+f"(d[9]), "+f"(d[10]), "+f"(d[11])
        : "r"(a0), "r"(a1), "r"(a2), "r"(a3), "l"(db));
}
__device__ __forceinline__ void wgmma_rs_n16_zero64(float (&d)[8], uint32_t a0, uint32_t a1, uint32_t a2, uint32_t a3, uint64_t db) {
    asm volatile("wgmma.mma_async.sync.aligned.m64n16k16.f32.bf16.bf16 {"
        "%0, %1, %2, %3, %4, %5, %6, %7}, "
        "{%8, %9, %10, %11}, %12, 0, 1, 1, 0;\n"
        : "+f"(d[0]), "+f"(d[1]), "+f"(d[2]), "+f"(d[3]), "+f"(d[4]), "+f"(d[5]), "+f"(d[6]), "+f"(d[7])
        : "r"(a0), "r"(a1), "r"(a2), "r"(a3), "l"(db));
}
__device__ __forceinline__ void wgmma_rs_n48_64(float (&d)[24], uint32_t a0, uint32_t a1, uint32_t a2, uint32_t a3, uint64_t db) {
    asm volatile("wgmma.mma_async.sync.aligned.m64n48k16.f32.bf16.bf16 {"
        "%0, %1, %2, %3, %4, %5, %6, %7, %8, %9, %10, %11, %12, %13, %14, %15 "
        "%16, %17, %18, %19, %20, %21, %22, %23}, "
        "{%24, %25, %26, %27}, %28, 1, 1, 1, 0;\n"
        : "+f"(d[0]), "+f"(d[1]), "+f"(d[2]), "+f"(d[3]), "+f"(d[4]), "+f"(d[5]), "+f"(d[6]), "+f"(d[7]),
          "+f"(d[8]), "+f"(d[9]), "+f"(d[10]), "+f"(d[11]), "+f"(d[12]), "+f"(d[13]), "+f"(d[14]), "+f"(d[15]),
          "+f"(d[16]), "+f"(d[17]), "+f"(d[18]), "+f"(d[19]), "+f"(d[20]), "+f"(d[21]), "+f"(d[22]), "+f"(d[23])
        : "r"(a0), "r"(a1), "r"(a2), "r"(a3), "l"(db));
}
template <uint32_t HI>
__device__ __forceinline__ void wgmma_rs_n24_tb(float (&d)[12], uint32_t a0, uint32_t a1, uint32_t a2, uint32_t a3, uint32_t db_lo) {
    asm volatile("{\n.reg .b64 dsc;\nmov.b64 dsc, {%16, %17};\n"
        "wgmma.mma_async.sync.aligned.m64n24k16.f32.bf16.bf16 {"
        "%0, %1, %2, %3, %4, %5, %6, %7, %8, %9, %10, %11}, "
        "{%12, %13, %14, %15}, dsc, 1, 1, 1, 1;\n}\n"
        : "+f"(d[0]), "+f"(d[1]), "+f"(d[2]), "+f"(d[3]), "+f"(d[4]), "+f"(d[5]), "+f"(d[6]), "+f"(d[7]),
          "+f"(d[8]), "+f"(d[9]), "+f"(d[10]), "+f"(d[11])
        : "r"(a0), "r"(a1), "r"(a2), "r"(a3), "r"(db_lo), "n"(HI));
}


constexpr int NSLOT = 4, NSTEP = 16;
__host__ __device__ constexpr int step_half(int t) { return t < 3 ? 0 : (t > 12 ? 1 : (t & 1)); }
__host__ __device__ constexpr int step_kb(int t) { return t < 3 ? t : (t > 12 ? t - 8 : ((t & 1) ? (t - 3) / 2 : (t + 2) / 2)); }
constexpr uint32_t XS_BYTES = 32768, WS_BYTES = 12288, WBUF = NSLOT * XS_BYTES;
constexpr uint32_t REC = 5120, RECD = REC / 16, KVA = 0, KVB = 32 * REC, BARS = 28 * 8192;
static_assert(KVB + 12 * REC <= BARS && KVB == 20 * 8192, "layout");
constexpr uint32_t FULL_BAR = BARS, EMPTY_BAR = BARS + 40, X_BAR = BARS + 80,
                   MISC = BARS + 96,
                   STATS = BARS + 128,
                   CONSTS = BARS + 192,
                   P3BAR = BARS + 320,
                   CP_BAR = P3BAR + 38 * 8,
                   KV_BAR = CP_BAR + 24,
                   W_BAR = KV_BAR + 16;
constexpr uint32_t SMEM1_BYTES = W_BAR + 64;
static_assert(WBUF + 8 * WS_BYTES <= BARS, "ring too large");

constexpr uint32_t KHI = (uint32_t)(make_desc(0, 1024, 128, 0) >> 32), VHI = (uint32_t)(make_desc(0, 128, 1024, 0) >> 32);
constexpr uint32_t dKA = (uint32_t)make_desc(SMEM_BASE + KVA, 1024, 128, 0), dVA = (uint32_t)make_desc(SMEM_BASE + KVA + 2048, 128, 1024, 0);
constexpr uint32_t dKB = (uint32_t)make_desc(SMEM_BASE + KVB, 1024, 128, 0), dVB = (uint32_t)make_desc(SMEM_BASE + KVB + 2048, 128, 1024, 0);

constexpr float QSCALE = 0.25f * 1.4426950408889634f;
constexpr float EXP_MAGIC = 381.401059f;

__device__ __forceinline__ uint32_t exp2_sw(float y0, float y1, uint32_t one2) {
    const uint32_t w = __byte_perm(__float_as_uint(y0), __float_as_uint(y1), 0x6521);
    uint32_t u, z;
    asm("lop3.b32 %0, %1, 0x007f007f, %2, 0xEA;" : "=r"(u) : "r"(w), "r"(one2));
    asm("fma.rn.bf16x2 %0, %1, %1, %2;" : "=r"(z) : "r"(u), "r"(0x40034003u));
    return w - u + z;
}

__device__ __forceinline__ void make_masks(uint32_t (&M)[9]) {
    uint32_t t;
    asm volatile("mov.u32 %0, %tid.x;" : "=r"(t));
    const int s0 = 16 - 16 * ((int)((t >> 1) & 48) + (int)((t >> 2) & 7) - 2 * (int)(t & 3));
    M[0] = 0; M[8] = 0xffffffffu;
#pragma unroll
    for (int i = 1; i < 8; i++) asm("shr.u32 %0, %1, %2;" : "=r"(M[i]) : "r"(0xffffffffu), "r"(max(s0 - 128 * (i - 7), 0)));
}

struct Scores { float m[8], p[24]; };

__device__ __forceinline__ void load_magic(Scores& S, int i, uint32_t caddr) {
    asm volatile("ld.volatile.shared.v4.f32 {%0, %1, %2, %3}, [%4];"
                 : "=f"(S.p[4 * i]), "=f"(S.p[4 * i + 1]), "=f"(S.p[4 * i + 2]), "=f"(S.p[4 * i + 3]) : "r"(caddr + 16 * i));
}
__device__ __forceinline__ void issue_qk(Scores& S, const uint32_t (&q)[4], uint32_t kd) {
    uint64_t kd64;
    asm("mov.b64 %0, {%1, %2};" : "=l"(kd64) : "r"(kd), "n"(KHI));
    wgmma_rs_n16_zero64(S.m, q[0], q[1], q[2], q[3], kd64);
    wgmma_rs_n48_64(S.p, q[0], q[1], q[2], q[3], kd64 + 16);
}

template <int MODE, bool QK>
__device__ __forceinline__ void attn_step(Scores& S, float (&O)[12], const uint32_t (&qn)[4], uint32_t kd_next, uint32_t vd,
                                          uint32_t one2, uint32_t caddr) {
    uint32_t P[16], M[9];
    if (MODE) make_masks(M);
#pragma unroll
    for (int i = 0; i < 4; i++) P[i] = pack_bf16(ex2(S.m[2 * i]), ex2(S.m[2 * i + 1]));
#pragma unroll
    for (int i = 0; i < 6; i++) {
        P[4 + 2 * i] = exp2_sw(S.p[4 * i], S.p[4 * i + 1], one2);
        P[5 + 2 * i] = exp2_sw(S.p[4 * i + 2], S.p[4 * i + 3], one2);
        if (QK) load_magic(S, i, caddr);
    }
#pragma unroll
    for (int i = 0; i < 16; i++) {
        if (MODE == 1) P[i] &= M[(i & 1) - (i >> 1) + 7];
        if (MODE == 2) P[i] &= ~M[(i & 1) - (i >> 1) + 7];
    }
    uint64_t vd64;
    asm("mov.b64 %0, {%1, %2};" : "=l"(vd64) : "r"(vd), "n"(VHI));
    fence_regs(P); fence_regs(S.p);
    wg_fence();
#pragma unroll
    for (int k = 0; k < 4; k++) wgmma_rs_n24_tb64(O, P[4 * k], P[4 * k + 1], P[4 * k + 2], P[4 * k + 3], vd64 + k * 16);
    if (QK) issue_qk(S, qn, kd_next);
    wg_commit();
    wg_wait<0>();
    fence_regs(S.m); fence_regs(S.p); fence_regs(P); fence_regs(O);
}

template <int UNR>
__device__ __forceinline__ void attn_run(Scores& S, float (&O)[12], const uint32_t (&q)[4], uint32_t vd, int n, uint32_t one2, uint32_t caddr) {
#pragma unroll 1
    for (const uint32_t vend = vd + n * RECD; vd != vend; vd += UNR * RECD) {
#pragma unroll
        for (int u = 0; u < UNR; u++) attn_step<0, true>(S, O, q, vd + (u + 1) * RECD + (dKA - dVA), vd + u * RECD, one2, caddr);
    }
}
__device__ __forceinline__ void zero_o(float (&O)[12]) {
#pragma unroll
    for (int i = 0; i < 12; i++) O[i] = 0.f;
    fence_regs(O);
}

__device__ __forceinline__ void attn_slow(float (&O)[12], const uint32_t (&q)[4], uint32_t kd, uint32_t vd,
                                          int ntiles, bool mask_first, bool mask_last) {
    const int lane = threadIdx.x & 31;
    const int dbase = ((threadIdx.x >> 5) & 3) * 16 + (lane >> 2) - 2 * (lane & 3);
    uint32_t P[16];
    float S[32];
    float m0 = -INFINITY, m1 = -INFINITY;
#pragma unroll
    for (int i = 0; i < 32; i++) S[i] = 0.f;
#pragma unroll
    for (int i = 0; i < 12; i++) O[i] = 0.f;
#pragma unroll 1
    for (int j = 0; j < ntiles; j++) {
        fence_regs(S);
        wg_fence();
        wgmma_rs_n64_zero<KHI>(S, q[0], q[1], q[2], q[3], kd + j * RECD);
        wg_commit();
        wg_wait<0>();
        fence_regs(S);
        const bool mf = mask_first && j == 0, ml = mask_last && j == ntiles - 1;
        if (mf || ml) {
#pragma unroll
            for (int i = 0; i < 32; i++) {
                const int d = dbase + 8 * ((i >> 1) & 1) - 8 * (i >> 2) - (i & 1);
                const bool keep = ml ? (d >= 0) : (d < 0);
                if (!keep) S[i] = -1e9f * 1.4426950408889634f;
            }
        }
        float x0 = m0, x1 = m1;
#pragma unroll
        for (int b = 0; b < 8; b++) {
            x0 = fmaxf(x0, fmaxf(S[4 * b], S[4 * b + 1]));
            x1 = fmaxf(x1, fmaxf(S[4 * b + 2], S[4 * b + 3]));
        }
        x0 = fmaxf(x0, __shfl_xor_sync(~0u, x0, 1)); x0 = fmaxf(x0, __shfl_xor_sync(~0u, x0, 2));
        x1 = fmaxf(x1, __shfl_xor_sync(~0u, x1, 1)); x1 = fmaxf(x1, __shfl_xor_sync(~0u, x1, 2));
        const float a0 = ex2(m0 - x0), a1 = ex2(m1 - x1);
        m0 = x0; m1 = x1;
#pragma unroll
        for (int b = 0; b < 3; b++) { O[4 * b] *= a0; O[4 * b + 1] *= a0; O[4 * b + 2] *= a1; O[4 * b + 3] *= a1; }
#pragma unroll
        for (int b = 0; b < 8; b++) {
            P[2 * b] = pack_bf16(ex2(S[4 * b] - m0), ex2(S[4 * b + 1] - m0));
            P[2 * b + 1] = pack_bf16(ex2(S[4 * b + 2] - m1), ex2(S[4 * b + 3] - m1));
        }
        fence_regs(P); fence_regs(O);
        wg_fence();
#pragma unroll
        for (int k = 0; k < 4; k++) wgmma_rs_n24_tb<VHI>(O, P[4 * k], P[4 * k + 1], P[4 * k + 2], P[4 * k + 3], vd + j * RECD + k * 16);
        wg_commit();
        wg_wait<0>();
        fence_regs(P); fence_regs(O);
    }
}

__device__ __forceinline__ bool shift_free_ok(float q2, float k2, float vlo, float vhi) {
    float b;
    asm("sqrt.approx.f32 %0, %1;" : "=f"(b) : "f"(q2 * k2));
    b = b * 1.02f + 1.f;
    const float e = ex2(b);
    return __all_sync(~0u, b <= 110.f && vhi * e <= 0x1p114f && vlo * 0x1p99f >= e);
}

__device__ __forceinline__ void store_o(const float (&O)[12], __nv_bfloat16* dst  ) {
    float i0, i1;
    asm("rcp.approx.ftz.f32 %0, %1;" : "=f"(i0) : "f"(O[8]));
    asm("rcp.approx.ftz.f32 %0, %1;" : "=f"(i1) : "f"(O[10]));
    *reinterpret_cast<uint32_t*>(dst) = pack_bf16(O[0] * i0, O[1] * i0);
    *reinterpret_cast<uint32_t*>(dst + 8) = pack_bf16(O[4] * i0, O[5] * i0);
    *reinterpret_cast<uint32_t*>(dst + 8 * 1024) = pack_bf16(O[2] * i1, O[3] * i1);
    *reinterpret_cast<uint32_t*>(dst + 8 * 1024 + 8) = pack_bf16(O[6] * i1, O[7] * i1);
}

__device__ __forceinline__ uint32_t absmax2(uint32_t a, uint32_t b) {
    uint32_t m;
    asm("max.NaN.xorsign.abs.bf16x2 %0, %1, %2;" : "=r"(m) : "r"(a), "r"(b));
    return m;
}
__device__ __forceinline__ uint32_t absmax4(const uint32_t* a) { return absmax2(absmax2(a[0], a[1]), absmax2(a[2], a[3])); }
__device__ __forceinline__ uint32_t absmax_warp(uint32_t a, uint32_t b) {
    const uint32_t m = absmax2(a, b);
    return __reduce_max_sync(~0u, max(m & 0x7fff0000u, (m << 16) & 0x7fff0000u));
}
__device__ __forceinline__ uint32_t up16(uint32_t fbits) { return min(fbits >> 16, 0x7ffeu) + 1u; }

__device__ __forceinline__ void cnt_release(uint32_t* p, uint32_t n) { asm volatile("red.release.gpu.global.add.u32 [%0], %1;" ::"l"(p), "r"(n) : "memory"); }
__device__ __forceinline__ void cnt_wait_warp(const uint32_t* p, uint32_t target) {
#pragma unroll 1
    for (uint32_t i = 0; i < (1u << 22); i++) {
        uint32_t v;
        asm volatile("ld.relaxed.gpu.global.u32 %0, [%1];" : "=r"(v) : "l"(p) : "memory");
        if (__all_sync(~0u, ((v ^ target) & 0xfffffu) == 0)) { asm volatile("fence.acquire.gpu;" ::: "memory"); return; }
    }
    __trap();
}

__device__ __forceinline__ void row_norm_part(const float (&a)[48], int i, float& s0, float& s1) {
    const float* p = a + 24 * (i >> 1) + 8 * (i & 1);
    s0 = (p[0] * p[0] + p[1] * p[1]) + (p[4] * p[4] + p[5] * p[5]);
    s1 = (p[2] * p[2] + p[3] * p[3]) + (p[6] * p[6] + p[7] * p[7]);
}
__device__ __forceinline__ void row_norm_stats(const float (&s)[4][4], int lane, uint32_t stats_addr) {
    float t[4][2];
    const bool o1 = lane & 1, o2 = lane & 2;
#pragma unroll
    for (int i = 0; i < 4; i++) {
        t[i][0] = (o1 ? s[i][1] : s[i][0]) + __shfl_xor_sync(~0u, o1 ? s[i][0] : s[i][1], 1);
        t[i][1] = (o1 ? s[i][3] : s[i][2]) + __shfl_xor_sync(~0u, o1 ? s[i][2] : s[i][3], 1);
    }
    uint32_t m[4];
#pragma unroll
    for (int i = 0; i < 4; i++) {
        const float v = (o2 ? t[i][1] : t[i][0]) + __shfl_xor_sync(~0u, o2 ? t[i][0] : t[i][1], 2);
        m[i] = __float_as_uint(v);
    }
#pragma unroll
    for (int i = 0; i < 4; i++) m[i] = __reduce_max_sync(~0u, m[i]);
    const uint32_t mv = o2 ? (o1 ? m[3] : m[2]) : (o1 ? m[1] : m[0]);
    if (lane < 4) asm volatile("red.shared.max.u32 [%0], %1;" ::"r"(stats_addr + 4 * lane), "r"(mv) : "memory");
}
__device__ __forceinline__ void finish_branch(float (&a)[48], int br, float (&s)[4][4], int mt, uint32_t (&q)[4], uint32_t (&kv)[16]) {
#pragma unroll
    for (int i = 0; i < 8; i++) a[24 * br + i] *= QSCALE;
    row_norm_part(a, 2 * br, s[2 * br][2 * mt], s[2 * br][2 * mt + 1]);
    row_norm_part(a, 2 * br + 1, s[2 * br + 1][2 * mt], s[2 * br + 1][2 * mt + 1]);
#pragma unroll
    for (int i = 0; i < 4; i++) q[i] = pack_bf16(a[24 * br + 2 * i], a[24 * br + 2 * i + 1]);
#pragma unroll
    for (int i = 0; i < 8; i++) kv[8 * br + i] = pack_bf16(a[24 * br + 8 + 2 * i], a[24 * br + 8 + 2 * i + 1]);
}

__global__ void __launch_bounds__(512, 1)
fused_kernel(const __grid_constant__ CUtensorMap tm_x, const __grid_constant__ CUtensorMap tm_wa,
             const __grid_constant__ CUtensorMap tm_wb,
             const __grid_constant__ CUtensorMap tm_woa4, const __grid_constant__ CUtensorMap tm_wob4,
             const __grid_constant__ CUtensorMap tm_o1, const __grid_constant__ CUtensorMap tm_o4,
             const __nv_bfloat16* __restrict__ x, const __nv_bfloat16* __restrict__ gate_w, __nv_bfloat16* __restrict__ out) {
    extern __shared__ __align__(1024) uint8_t sp[];
    const uint32_t sb = smem_u32(sp);
    if ((sb & 0x3FFFF) != SMEM_BASE) __trap();
    const int tid = threadIdx.x, lane = tid & 31;
    const int warp = __shfl_sync(~0u, tid >> 5, 0), wg = warp >> 2, w4 = warp & 3;
    const int bid = blockIdx.x, rank = bid & 1, qb = (bid >> 1) & 3, head = ((bid >> 3) << 1) | rank;
    const int slot = head * 4 + qb;

    if (tid == 128) {
        asm volatile("prefetch.tensormap [%0];" ::"l"(&tm_wa) : "memory");
        asm volatile("prefetch.tensormap [%0];" ::"l"(&tm_wb) : "memory");
    }
    if (tid == 0) {
        for (int s = 0; s < NSLOT; s++) mbar_init(sb + FULL_BAR + 8 * s, 1);
        for (int s = 0; s < 3; s++) mbar_init(sb + W_BAR + 8 * s, 1);
        asm volatile("fence.mbarrier_init.release.cluster;" ::: "memory");
        for (int t = 0; t < 4; t++) {
            mbar_expect_tx(sb + FULL_BAR + 8 * t, XS_BYTES);
            tma_2d(sb + t * XS_BYTES, &tm_x, step_kb(t) * 64, qb * 512 + step_half(t) * 256, sb + FULL_BAR + 8 * t);
            if (t < 3) {
                mbar_expect_tx(sb + W_BAR + 8 * t, WS_BYTES);
                tma_4d(sb + WBUF + (7 - t) * WS_BYTES, &tm_wa, 0, t * 64, head, 0, sb + W_BAR + 8 * t);
                tma_4d(sb + WBUF + (7 - t) * WS_BYTES + 6144, &tm_wb, 0, t * 64, head, 0, sb + W_BAR + 8 * t);
            }
        }
    }
    if (tid == 256) {
        for (int s = 0; s < NSLOT; s++) mbar_init(sb + EMPTY_BAR + 8 * s, 8);
        for (int s = 3; s < 8; s++) mbar_init(sb + W_BAR + 8 * s, 1);
        mbar_init(sb + X_BAR, 3);
        asm volatile("fence.mbarrier_init.release.cluster;" ::: "memory");
    }
    if (tid >= 32 && tid < 48) {
        if (tid != 37) reinterpret_cast<uint32_t*>(sp + MISC)[tid - 32] = tid == 36 ? 0xbf80bf80u : 0u;
    }
    if (tid >= 64 && tid < 88) reinterpret_cast<float*>(sp + CONSTS)[tid - 64] = EXP_MAGIC;
    __syncthreads();
    asm volatile("barrier.cluster.arrive.relaxed.aligned;" ::: "memory");

    uint32_t qa0[4], qa1[4], qb0[4], qb1[4];
    uint4* const qs = g_qsave + bid * 3584 + tid;
    const uint32_t caddr = sb + CONSTS;
    Scores S;
    {
        float acc0[48], acc1[48], nrm[4][4];
        uint32_t kv0[16], kv1[16], vmx[2];
        uint4 gx[2], gw[2];
        uint32_t cnt0;
        const int grow = qb * 512 + head * 16 + warp;
#pragma unroll
        for (int c = 0; c < 2; c++) {
            gx[c] = __ldg(reinterpret_cast<const uint4*>(x + (size_t)grow * DM) + lane + 32 * c);
            gw[c] = __ldg(reinterpret_cast<const uint4*>(gate_w) + lane + 32 * c);
        }
        asm volatile("ld.relaxed.gpu.global.u32 %0, [%1];" : "=r"(cnt0) : "l"(&g_cnt[1][qb * 32]) : "memory");
        const uint32_t ra = sb + KVA + wg * REC + (w4 * 16 + (lane & 15)) * 16 + (lane >> 4) * 1024, rb = ra + (KVB + 4 * REC - KVA);
        const uint64_t da0 = make_desc(SMEM_BASE + wg * 8192, 16, 1024, 1);
        constexpr uint64_t db0 = make_desc(SMEM_BASE + WBUF, 2048, 256, 3);
#pragma unroll
        for (int t = 0; t < NSTEP; t++) {
            const int s = t % NSLOT, hf = step_half(t), kb = step_kb(t);
            if (hf == 0) mbar_wait_warp(sb + W_BAR + 8 * kb, 0);
            mbar_wait_warp(sb + FULL_BAR + 8 * s, (t / NSLOT) & 1);
            const uint64_t da = da0 + (uint64_t)(s * (XS_BYTES >> 4)), db = db0 + (uint64_t)((7 - kb) * (WS_BYTES >> 4));
            wg_fence();
#pragma unroll
            for (int k = 0; k < 4; k++) {
                if (kb == 0 && k == 0) wgmma_ss_n96_tb_zero(hf ? acc1 : acc0, da, db);
                else wgmma_ss_n96_tb(hf ? acc1 : acc0, da + 2 * k, db + 32 * k);
            }
            wg_commit();
            if (t >= 1 && t <= 14) wg_wait<1>();
            if (t >= 1 && t - 1 + NSLOT < NSTEP) {
                const int ps = (t - 1) % NSLOT, nt = t - 1 + NSLOT;
                if (w4 == 3 && lane == 0) mbar_arrive_cluster(sb + EMPTY_BAR + 8 * ps, nt & 1);
                if (tid == 0 && step_half(nt) == 0) {
                    const int nk = step_kb(nt);
                    mbar_expect_tx(sb + W_BAR + 8 * nk, WS_BYTES);
                    tma_4d(sb + WBUF + (7 - nk) * WS_BYTES, &tm_wa, 0, nk * 64, head, 0, sb + W_BAR + 8 * nk);
                    tma_4d(sb + WBUF + (7 - nk) * WS_BYTES + 6144, &tm_wb, 0, nk * 64, head, 0, sb + W_BAR + 8 * nk);
                }
                __syncwarp();
                if (warp == 0 && (nt & 1) == rank) mbar_wait_warp(sb + EMPTY_BAR + 8 * ps, ((t - 1) / NSLOT) & 1);
                if (tid == 0) {
                    mbar_expect_tx(sb + FULL_BAR + 8 * ps, XS_BYTES);
                    if ((nt & 1) == rank)
                        tma_2d_mc(sb + ps * XS_BYTES, &tm_x, step_kb(nt) * 64, qb * 512 + step_half(nt) * 256, sb + FULL_BAR + 8 * ps, 3);
                }
                __syncwarp();
            }
            if (t == 0) asm volatile("barrier.cluster.wait.aligned;" ::: "memory");
            if (t == 1) {
                float ga = 0.f, gb = 0.f;
#pragma unroll
                for (int c = 0; c < 2; c++) {
                    const uint32_t av[4] = {gx[c].x, gx[c].y, gx[c].z, gx[c].w}, gv[4] = {gw[c].x, gw[c].y, gw[c].z, gw[c].w};
#pragma unroll
                    for (int i = 0; i < 4; i++) {
                        ga += __uint_as_float(av[i] << 16) * __uint_as_float(gv[i] << 16);
                        gb += __uint_as_float(av[i] & 0xffff0000u) * __uint_as_float(gv[i] & 0xffff0000u);
                    }
                }
                gx[0].x = __float_as_uint(ga + gb);
            }
            if (t == 2) {
                float ga = __uint_as_float(gx[0].x);
#pragma unroll
                for (int o = 16; o; o >>= 1) ga += __shfl_xor_sync(~0u, ga, o);
                if (lane == 0) g_gate[grow] = __fdividef(1.f, 1.f + __expf(-ga));
                if (tid == 37) reinterpret_cast<uint32_t*>(sp + MISC)[5] = cnt0;
            }
            if (t >= 4 && t < 8 && tid == 128 * (t - 4) + 32) {
#pragma unroll
                for (int i = 11 * (t - 4); i < 11 * (t - 3) && i < 43; i++) mbar_init(sb + P3BAR + 8 * i, i >= 41 ? 16 : (i >= 38 ? 4 : (i >= 30 ? 2 : 1)));
            }
            if (t == 13) {
                fence_regs(acc0);
                finish_branch(acc0, 1, nrm, 0, qb0, kv0);
                qs[2 * 512] = make_uint4(qb0[0], qb0[1], qb0[2], qb0[3]);
            }
            if (t == 14) {
                finish_branch(acc0, 0, nrm, 0, qa0, kv0);
            }
            if (t == 15) {
                __syncthreads();
                stmatrix_x4(ra, kv0[0], kv0[1], kv0[2], kv0[3]);
                stmatrix_x4(ra + 2048, kv0[4], kv0[5], kv0[6], kv0[7]);
                stmatrix_x4(rb, kv0[8], kv0[9], kv0[10], kv0[11]);
                stmatrix_x4(rb + 2048, kv0[12], kv0[13], kv0[14], kv0[15]);
                uint8_t* const op = sp + KVA + (wg + ((tid >> 4) & 4)) * REC + 4096 + (tid & 63) * 16;
                *reinterpret_cast<uint4*>(op) = make_uint4(0x3f803f80u, 0x3f803f80u, 0x3f803f80u, 0x3f803f80u);
                *reinterpret_cast<uint4*>(op + (KVB + 4 * REC - KVA)) = make_uint4(0x3f803f80u, 0x3f803f80u, 0x3f803f80u, 0x3f803f80u);
                vmx[0] = absmax4(kv0 + 4); vmx[1] = absmax4(kv0 + 12);
                fence_async_smem();
                asm volatile("bar.sync %0, 128;" ::"r"(wg + 1) : "memory");
            }
        }
        wg_wait<0>();
        fence_regs(acc1);
        finish_branch(acc1, 1, nrm, 1, qb1, kv1);
        finish_branch(acc1, 0, nrm, 1, qa1, kv1);
        fence_regs(kv1); fence_regs(qa1); fence_regs(nrm[0]); fence_regs(nrm[1]); fence_regs(nrm[2]); fence_regs(nrm[3]);
#pragma unroll
        for (int i = 0; i < 8; i++) S.m[i] = 0.f;
#pragma unroll
        for (int i = 0; i < 6; i++) load_magic(S, i, caddr);
        fence_regs(S.m); fence_regs(S.p);
        wg_fence();
        issue_qk(S, qb1, dKB + (wg + 4) * RECD);
        wg_commit();
        stmatrix_x4(rb + 4 * REC, kv1[8], kv1[9], kv1[10], kv1[11]);
        stmatrix_x4(rb + 4 * REC + 2048, kv1[12], kv1[13], kv1[14], kv1[15]);
        stmatrix_x4(ra + 4 * REC, kv1[0], kv1[1], kv1[2], kv1[3]);
        stmatrix_x4(ra + 4 * REC + 2048, kv1[4], kv1[5], kv1[6], kv1[7]);
        fence_async_smem();
        __syncwarp();
        if (lane == 0) mbar_arrive(sb + KV_BAR);
        row_norm_stats(nrm, lane, sb + STATS);
        {
            const uint32_t va = absmax_warp(vmx[0], absmax4(kv1 + 4)), vb = absmax_warp(vmx[1], absmax4(kv1 + 12));
            if (lane < 2) asm volatile("red.shared.max.u32 [%0], %1;" ::"r"(sb + STATS + 16 + 4 * lane), "r"(lane ? vb : va) : "memory");
        }
        __syncwarp();
        if (lane == 0) mbar_arrive(sb + KV_BAR + 8);
        wg_wait<0>();
        fence_regs(S.m); fence_regs(S.p);
        mbar_wait_warp(sb + KV_BAR, 0);
    }
    if (tid == 384) {
        uint8_t* dst = g_kv + (size_t)slot * 61440;
        bulk_s2g(dst, sb + KVA, 8 * REC);
        bulk_s2g(dst + 8 * REC, sb + KVB + 8 * REC, 4 * REC);
        asm volatile("cp.async.bulk.commit_group;" ::: "memory");
    }
    __syncwarp();

    const uint32_t one2 = *reinterpret_cast<volatile uint32_t*>(sp + MISC + 16);
    const float* st = reinterpret_cast<const float*>(sp + STATS);
    __nv_bfloat16* const obase = g_ocat + (size_t)(qb * 512 + wg * 64 + w4 * 16 + (lane >> 2)) * 1024 + head * 16 + 2 * (lane & 3);
    float O[12];
    auto load_q = [&](uint32_t (&q)[4], int job) {
        asm volatile("ld.global.v4.u32 {%0, %1, %2, %3}, [%4];" : "=r"(q[0]), "=r"(q[1]), "=r"(q[2]), "=r"(q[3]) : "l"(qs + job * 512) : "memory");
    };
    const uint32_t* const stu = reinterpret_cast<const uint32_t*>(sp + STATS);
    auto cnt_target = [&]() { return *reinterpret_cast<const uint32_t*>(sp + MISC + 20) + 32u; };
    const int rowE = qb * 512 + 256 + (head >> 3) * 64, rowL = rowE - 256, n0 = (head & 7) * 64;
    auto p3_load_w = [&](int g) {
        mbar_expect_tx(sb + P3BAR + 8 * g, 32768);
        tma_2d(sb + (g == 0 ? 0 : g == 3 ? 4 : 16 + 4 * g) * 8192, g < 2 ? &tm_wob4 : &tm_woa4, n0, (g & 1) * 256, sb + P3BAR + 8 * g);
    };
    auto p3_load_o = [&](int late) {
        mbar_expect_tx(sb + P3BAR + 8 * (4 + late), 32768);
        tma_3d(sb + (8 + 4 * late) * 8192, &tm_o4, 0, late ? rowL : rowE, 8, sb + P3BAR + 8 * (4 + late));
    };
    auto save_q = [&](const uint32_t (&q)[4], int job) { qs[job * 512] = make_uint4(q[0], q[1], q[2], q[3]); };
    zero_o(O);
    if (__all_sync(~0u, one2 != 0))
        attn_step<2, true>(S, O, qb1, dKB + (wg + 5) * RECD, dVB + (wg + 4) * RECD, one2, caddr);
    mbar_wait_warp(sb + KV_BAR + 8, 0);
    const bool fast = shift_free_ok(st[0], st[1], st[4], st[4]) & shift_free_ok(st[2], st[3], st[5], st[5]);
    uint32_t redo = fast ? 0 : 15;
    {
        const uint32_t vd = dVB + (wg + 4) * RECD;
        if (fast) {
            attn_run<1>(S, O, qb1, vd + RECD, 3, one2, caddr);
        }
        if (tid == 384) {
            const unsigned long long fv = ((unsigned long long)((cnt_target() << 11) | up16(max(stu[4], stu[5]))) << 32) | (up16(stu[3]) << 16) | up16(stu[1]);
            asm volatile("cp.async.bulk.wait_group 0;" ::: "memory");
            asm volatile("st.relaxed.gpu.global.u64 [%0], %1;" ::"l"(g_flag + slot), "l"(fv) : "memory");
        }
        __syncwarp();
        save_q(qb1, 3);
        if (fast) {
            attn_step<1, true>(S, O, qa0, dKA, vd + 4 * RECD, one2, caddr);
            store_o(O, obase + 256 * 1024 + 512);
        }
    }
    {
        const int os = head * 4 + ((qb + wg + 1) & 3);
        const bool fetcher = w4 == 0 && wg < 3;
        auto poll = [&]() -> unsigned long long {
            unsigned long long f;
            asm volatile("ld.relaxed.gpu.global.u64 %0, [%1];" : "=l"(f) : "l"(g_flag + os) : "memory");
            return f;
        };
        if (fast) {
            zero_o(O);
            attn_step<0, true>(S, O, qa0, dKA + RECD, dVA, one2, caddr);
            attn_step<0, true>(S, O, qa0, dKA + 2 * RECD, dVA + RECD, one2, caddr);
        }
        unsigned long long f = 0;
        if (fetcher) f = poll();
        if (fast) {
            attn_step<0, true>(S, O, qa0, dKA + 3 * RECD, dVA + 2 * RECD, one2, caddr);
            attn_step<0, true>(S, O, qa0, dKA + 4 * RECD, dVA + 3 * RECD, one2, caddr);
        }
        if (fetcher) {
            const uint32_t tag = (cnt_target() >> 5) & 0xffffu;
#pragma unroll 1
            for (uint32_t i = 0; !__all_sync(~0u, (uint32_t)(f >> 48) == tag); i++) {
                if (i == (1u << 22)) __trap();
                f = poll();
            }
        }
        if (fetcher && lane == 0) {
            asm volatile("fence.acquire.gpu;" ::: "memory");
            asm volatile("fence.proxy.async.global;" ::: "memory");
            const bool halo = wg == 2 && qb > 0;
            *reinterpret_cast<unsigned long long*>(sp + STATS + 32 + wg * 8) = f;
            mbar_expect_tx(sb + X_BAR, halo ? 12 * REC : 8 * REC);
            const uint8_t* src = g_kv + (size_t)os * 61440;
            bulk_g2s(sb + KVA + (wg + 1) * 8 * REC, src, 8 * REC, sb + X_BAR);
            if (halo) bulk_g2s(sb + KVB, src + 8 * REC, 4 * REC, sb + X_BAR);
        }
        __syncwarp();
        if (fast) {
            attn_step<0, true>(S, O, qa0, dKA + 5 * RECD, dVA + 4 * RECD, one2, caddr);
            attn_step<0, true>(S, O, qa0, dKA + 6 * RECD, dVA + 5 * RECD, one2, caddr);
        }
        if (fast) {
            attn_step<0, true>(S, O, qa0, dKA + 7 * RECD, dVA + 6 * RECD, one2, caddr);
            attn_step<0, true>(S, O, qa1, dKA, dVA + 7 * RECD, one2, caddr);
#pragma unroll
            for (int i = 0; i < 3; i++)
                qs[(4 + i) * 512] = make_uint4(__float_as_uint(O[4 * i]), __float_as_uint(O[4 * i + 1]), __float_as_uint(O[4 * i + 2]), __float_as_uint(O[4 * i + 3]));
        }
    }
    save_q(qa0, 0);
    const int first = qb > 0 ? 0 : 4 - wg;
    {
        if (fast) {
            zero_o(O);
            attn_run<2>(S, O, qa1, dVA, 6, one2, caddr);
        }
        mbar_wait_warp(sb + X_BAR, 0);
        save_q(qa1, 1);
        {
            const uint32_t ka = max(stu[1], max(stu[8] << 16, max(stu[10] << 16, stu[12] << 16)));
            const uint32_t va = max(stu[4], max(stu[9] << 16, max(stu[11] << 16, stu[13] << 16)));
            if (!shift_free_ok(st[0], __uint_as_float(ka), st[4], __uint_as_float(va))) redo |= 3;
            if (!shift_free_ok(st[2], __uint_as_float(max(stu[3], stu[12] & 0xffff0000u)), st[5], __uint_as_float(max(stu[5], stu[13] << 16)))) redo |= 4;
        }
        if (fast) {
            attn_run<2>(S, O, qa1, dVA + 6 * RECD, 24, one2, caddr);
            load_q(qb0, 2);
            attn_step<0, true>(S, O, qa1, dKA + 31 * RECD, dVA + 30 * RECD, one2, caddr);
            attn_step<0, true>(S, O, qb0, dKB + (wg + first) * RECD, dVA + 31 * RECD, one2, caddr);
            store_o(O, obase + 256 * 1024);
        }
    }
    if (fast) {
        uint32_t vd = dVB + (wg + first) * RECD;
        zero_o(O);
        if (qb > 0) { attn_step<2, true>(S, O, qb0, vd + RECD + (dKA - dVA), vd, one2, caddr); vd += RECD; }
        load_q(qa0, 0);
        attn_run<1>(S, O, qb0, vd, qb > 0 ? 3 : wg, one2, caddr);
        attn_step<1, true>(S, O, qa0, dKA + 8 * RECD, dVB + (wg + 4) * RECD, one2, caddr);
        store_o(O, obase + 512);
    }
    const bool pf = !redo;
    if (pf) asm volatile("bar.arrive 7, 544;" ::: "memory");
    auto checkpoint = [&](int i) { if (pf && w4 == 3 && lane == 0) mbar_arrive(sb + CP_BAR + 8 * i); };
    if (fast) {
#pragma unroll
        for (int i = 0; i < 3; i++)
            asm volatile("ld.global.v4.f32 {%0, %1, %2, %3}, [%4];" : "=f"(O[4 * i]), "=f"(O[4 * i + 1]), "=f"(O[4 * i + 2]), "=f"(O[4 * i + 3]) : "l"(qs + (4 + i) * 512) : "memory");
        attn_run<2>(S, O, qa0, dVA + 8 * RECD, 6, one2, caddr);
        checkpoint(0);
        if (pf && warp == 15) {
            asm volatile("bar.sync 7, 544;" ::: "memory");
            if (lane == 0) cnt_release(&g_cnt[0][qb * 32], 1);
            __syncwarp();
        }
        attn_run<2>(S, O, qa0, dVA + 14 * RECD, 8, one2, caddr);
        if (pf && warp == 11) {
            mbar_wait_warp(sb + CP_BAR, 0);
            if (lane == 0) { p3_load_w(0); p3_load_w(1); p3_load_w(2); p3_load_w(3); }
            __syncwarp();
        }
        if (pf && warp == 7) cnt_wait_warp(&g_cnt[0][qb * 32], cnt_target());
        checkpoint(1);
        attn_run<2>(S, O, qa0, dVA + 22 * RECD, 6, one2, caddr);
        checkpoint(2);
        if (pf && warp == 11) {
            mbar_wait_warp(sb + CP_BAR + 8, 0);
            if (lane == 0) { asm volatile("fence.proxy.async.global;" ::: "memory"); p3_load_o(0); }
            __syncwarp();
        }
        attn_step<0, true>(S, O, qa0, dKA + 29 * RECD, dVA + 28 * RECD, one2, caddr);
        attn_step<0, true>(S, O, qa0, dKA + 30 * RECD, dVA + 29 * RECD, one2, caddr);
        if (pf && warp == 15) {
            mbar_wait_warp(sb + CP_BAR + 16, 0);
            if (lane == 0) { asm volatile("fence.proxy.async.global;" ::: "memory"); p3_load_o(1); }
            __syncwarp();
        }
        attn_step<0, true>(S, O, qa0, dKA + 31 * RECD, dVA + 30 * RECD, one2, caddr);
        attn_step<0, false>(S, O, qa0, 0, dVA + 31 * RECD, one2, caddr);
        store_o(O, obase);
    }
#pragma unroll 1
    for (int job = 0; redo >> job; job++) {
        if (!((redo >> job) & 1)) continue;
        const uint4 qv = qs[job * 512];
        const uint32_t q[4] = {qv.x, qv.y, qv.z, qv.w};
        const int f0 = job == 2 ? first : 0;
        const uint32_t off = (wg + (job & 1) * 4 + f0) * RECD;
        const bool isb = job >= 2;
        attn_slow(O, q, isb ? dKB + off : dKA, isb ? dVB + off : dVA, isb ? 5 - f0 : 32, isb && f0 == 0, isb);
        store_o(O, obase + (job & 1) * 256 * 1024 + (isb ? 512 : 0));
    }
    __syncthreads();

    if (wg >= 2) {
        if (warp == 12) {
            if (lane == 0) {
                if (redo) cnt_release(&g_cnt[0][qb * 32], 1);
                cnt_release(&g_cnt[1][qb * 32], 1);
            }
            __syncwarp();
            cnt_wait_warp(&g_cnt[1][qb * 32], cnt_target());
            if (lane == 0) {
                asm volatile("fence.proxy.async.global;" ::: "memory");
#pragma unroll 1
                for (int i = 0; i < 8; i++) {
                    mbar_wait(sb + P3BAR + 8 * (30 + i), 0);
                    mbar_expect_tx(sb + P3BAR + 8 * (22 + i), 8192);
                    tma_2d(sb + (i < 4 ? 12 + i : i - 4) * 8192, &tm_o1, i * 64, rowL, sb + P3BAR + 8 * (22 + i));
                }
            }
        }
        if (warp == 8) {
            if (redo) {
                if (lane == 0) { p3_load_w(0); p3_load_w(1); p3_load_w(2); p3_load_w(3); }
                __syncwarp();
                cnt_wait_warp(&g_cnt[0][qb * 32], cnt_target());
            }
            if (lane == 0) {
                asm volatile("fence.proxy.async.global;" ::: "memory");
                if (redo) { p3_load_o(0); p3_load_o(1); }
#pragma unroll 1
                for (int i = 0; i < 4; i++) {
                    mbar_expect_tx(sb + P3BAR + 8 * (6 + i), 8192);
                    tma_2d(sb + (16 + i) * 8192, &tm_o1, (12 + i) * 64, rowE, sb + P3BAR + 8 * (6 + i));
                }
#pragma unroll 1
                for (int i = 0; i < 8; i++) {
                    mbar_wait(sb + P3BAR + 8 * (30 + i), 0);
                    if (i < 4) {
                        mbar_expect_tx(sb + P3BAR + 8 * (10 + i), 8192);
                        tma_2d(sb + i * 8192, &tm_o1, (12 + i) * 64, rowL, sb + P3BAR + 8 * (10 + i));
                    }
                    mbar_expect_tx(sb + P3BAR + 8 * (14 + i), 8192);
                    tma_2d(sb + (i < 4 ? 8 + i : 12 + i) * 8192, &tm_o1, i * 64, rowE, sb + P3BAR + 8 * (14 + i));
                }
            }
        }
        return;
    }
    {
        float accA[32], accB[32];
#pragma unroll
        for (int i = 0; i < 32; i++) { accA[i] = 0.f; accB[i] = 0.f; }
        fence_regs(accA); fence_regs(accB);
        constexpr uint64_t da0 = make_desc(SMEM_BASE, 16, 1024, 1);
        constexpr uint64_t db0 = make_desc(SMEM_BASE, 8192, 1024, 1);
        const int row = (wg ? rowL : rowE) + w4 * 16;
        float g0 = 0.f, g1 = 0.f;
#pragma unroll
        for (int kb = 0; kb < 16; kb++) {
            const int j = kb & 7;
            const int wslot = kb < 4 ? kb : (kb < 12 ? 16 + kb : kb - 8);
            const int oslot = wg ? (j < 4 ? 12 + j : j - 4) : (j < 4 ? 8 + j : 12 + j);
            if ((kb & 3) == 0) mbar_wait_warp(sb + P3BAR + 8 * (kb >> 2), 0);
            if (kb >= 8) mbar_wait_warp(sb + P3BAR + 8 * (14 + j) + wg * 64, 0);
            else if (kb == 0) mbar_wait_warp(sb + P3BAR + 8 * (4 + wg), 0);
            else if (kb >= 4) mbar_wait_warp(sb + P3BAR + 8 * (2 + kb) + wg * 32, 0);
            if (kb == 0) {
                asm volatile("ld.relaxed.gpu.global.f32 %0, [%1];" : "=f"(g0) : "l"(g_gate + row + (lane >> 2)) : "memory");
                asm volatile("ld.relaxed.gpu.global.f32 %0, [%1];" : "=f"(g1) : "l"(g_gate + row + (lane >> 2) + 8) : "memory");
            }
            const uint64_t da = da0 + (uint64_t)(oslot * 512), db = db0 + (uint64_t)(wslot * 512);
            wg_fence();
#pragma unroll
            for (int k = 0; k < 4; k++) {
                if (kb < 8) wgmma_ss_n64_tb(accB, da + 2 * k, db + 128 * k);
                else wgmma_ss_n64_tb(accA, da + 2 * k, db + 128 * k);
            }
            wg_commit();
            if (kb == 7) wg_wait<0>(); else if (kb >= 1 && kb < 7) wg_wait<1>();
            if (kb >= 1 && kb < 8) {
                if (w4 == 0 && lane == 0) {
                    mbar_arrive(sb + P3BAR + 8 * (30 + kb - 1));
                    if (kb == 7) mbar_arrive(sb + P3BAR + 8 * 37);
                }
                __syncwarp();
            }
        }
        wg_wait<0>();
        fence_regs(accA); fence_regs(accB);
        const uint32_t toff = (8 + wg * 4) * 8192 + w4 * 2048;
        const int mrow = (lane & 7) + ((lane >> 3) & 1) * 8;
#pragma unroll
        for (int p = 0; p < 4; p++) {
            uint32_t r[4];
#pragma unroll
            for (int h = 0; h < 2; h++) {
                const int i = (2 * p + h) * 4;
                r[2 * h] = pack_bf16(g0 * accA[i] + (1.f - g0) * accB[i], g0 * accA[i + 1] + (1.f - g0) * accB[i + 1]);
                r[2 * h + 1] = pack_bf16(g1 * accA[i + 2] + (1.f - g1) * accB[i + 2], g1 * accA[i + 3] + (1.f - g1) * accB[i + 3]);
            }
            const int chunk = 2 * p + (lane >> 4);
            stmatrix_x4(sb + toff + mrow * 128 + ((chunk ^ (mrow & 7)) << 4), r[0], r[1], r[2], r[3]);
        }
        __syncwarp();
#pragma unroll
        for (int p = 0; p < 4; p++) {
            const int r = p * 4 + (lane >> 3), c = lane & 7;
            const uint4 v = *reinterpret_cast<const uint4*>(sp + toff + r * 128 + ((c ^ (r & 7)) << 4));
            *reinterpret_cast<uint4*>(out + (size_t)(row + r) * DM + n0 + c * 8) = v;
        }
    }
}

typedef CUresult (*EncodeFn)(CUtensorMap*, CUtensorMapDataType, cuuint32_t, void*, const cuuint64_t*, const cuuint64_t*,
                             const cuuint32_t*, const cuuint32_t*, CUtensorMapInterleave, CUtensorMapSwizzle,
                             CUtensorMapL2promotion, CUtensorMapFloatOOBfill);

void encode(EncodeFn fn, CUtensorMap* tm, const void* ptr, int rank, const cuuint64_t* dims, const cuuint64_t* strides,
            const cuuint32_t* box, CUtensorMapSwizzle swz) {
    const cuuint32_t es[4] = {1, 1, 1, 1};
    fn(tm, CU_TENSOR_MAP_DATA_TYPE_BFLOAT16, rank, const_cast<void*>(ptr), dims, strides, box, es, CU_TENSOR_MAP_INTERLEAVE_NONE,
       swz, CU_TENSOR_MAP_L2_PROMOTION_L2_256B, CU_TENSOR_MAP_FLOAT_OOB_FILL_NONE);
}

}

extern "C" void kernel_launch(void* const* d_in, const int* in_sizes, int n_in, void* d_out, int out_size) {
    (void)in_sizes; (void)n_in; (void)out_size;
    const __nv_bfloat16* x = (const __nv_bfloat16*)d_in[0];
    const __nv_bfloat16* gate_w = (const __nv_bfloat16*)d_in[6];
    static EncodeFn fn = nullptr;
    static void* ocat = nullptr;
    if (!fn) {
        cudaDriverEntryPointQueryResult qr;
        cudaGetDriverEntryPoint("cuTensorMapEncodeTiled", (void**)&fn, cudaEnableDefault, &qr);
        cudaGetSymbolAddress(&ocat, g_ocat);
        cudaFuncSetAttribute(fused_kernel, cudaFuncAttributeMaxDynamicSharedMemorySize, SMEM1_BYTES);
    }
    CUtensorMap tm_x, tm_wa, tm_wb, tm_woa4, tm_wob4, tm_o1, tm_o4;
    {
        const cuuint64_t dims[2] = {512, 2048}, str[1] = {1024};
        const cuuint32_t box[2] = {64, 256};
        encode(fn, &tm_x, x, 2, dims, str, box, CU_TENSOR_MAP_SWIZZLE_128B);
    }
    {
        const cuuint64_t dims[4] = {16, 512, 32, 3}, str[3] = {3072, 32, 1024};
        const cuuint32_t box[4] = {16, 64, 1, 3};
        encode(fn, &tm_wa, d_in[1], 4, dims, str, box, CU_TENSOR_MAP_SWIZZLE_32B);
        encode(fn, &tm_wb, d_in[4], 4, dims, str, box, CU_TENSOR_MAP_SWIZZLE_32B);
    }
    {
        const cuuint64_t dims[2] = {1024, 2048}, str[1] = {2048};
        const cuuint32_t box[2] = {64, 64};
        encode(fn, &tm_o1, ocat, 2, dims, str, box, CU_TENSOR_MAP_SWIZZLE_128B);
        const cuuint64_t dims3[3] = {64, 2048, 16}, str3[2] = {2048, 128};
        const cuuint32_t box3[3] = {64, 64, 4};
        encode(fn, &tm_o4, ocat, 3, dims3, str3, box3, CU_TENSOR_MAP_SWIZZLE_128B);
    }
    {
        const cuuint64_t dims[2] = {512, 512}, str[1] = {1024};
        const cuuint32_t box4[2] = {64, 256};
        encode(fn, &tm_woa4, d_in[2], 2, dims, str, box4, CU_TENSOR_MAP_SWIZZLE_128B);
        encode(fn, &tm_wob4, d_in[5], 2, dims, str, box4, CU_TENSOR_MAP_SWIZZLE_128B);
    }
    cudaLaunchAttribute at[1];
    at[0].id = cudaLaunchAttributeClusterDimension;
    at[0].val.clusterDim.x = 2; at[0].val.clusterDim.y = 1; at[0].val.clusterDim.z = 1;
    cudaLaunchConfig_t cfg = {};
    cfg.gridDim = dim3(128); cfg.blockDim = dim3(512); cfg.dynamicSmemBytes = SMEM1_BYTES;
    cfg.stream = cudaStreamPerThread; cfg.attrs = at; cfg.numAttrs = 1;
    cudaLaunchKernelEx(&cfg, fused_kernel, tm_x, tm_wa, tm_wb, tm_woa4, tm_wob4, tm_o1, tm_o4, x, gate_w, (__nv_bfloat16*)d_out);
}
```

```cpp
#include <cuda_runtime.h>
#include <cuda_bf16.h>
#include <cuda.h>
#include <stdint.h>

namespace {

constexpr int SEQ = 2048, DM = 512;

__device__ __align__(1024) uint8_t g_kv[128 * 61440];
__device__ unsigned long long g_flag[128];
__device__ uint32_t g_cnt[2][4 * 32];
__device__ uint4 g_qsave[128 * 7 * 512];
__device__ float g_gate[SEQ];
__device__ __align__(1024) __nv_bfloat16 g_ocat[SEQ * 1024];

__device__ __forceinline__ uint32_t smem_u32(const void* p) { return (uint32_t)__cvta_generic_to_shared(p); }
__device__ __forceinline__ void wg_fence() { asm volatile("wgmma.fence.sync.aligned;" ::: "memory"); }
__device__ __forceinline__ void wg_commit() { asm volatile("wgmma.commit_group.sync.aligned;" ::: "memory"); }
template <int N> __device__ __forceinline__ void wg_wait() { asm volatile("wgmma.wait_group.sync.aligned %0;" ::"n"(N) : "memory"); }
constexpr uint32_t SMEM_BASE = 1024;
__host__ __device__ constexpr uint64_t make_desc(uint32_t addr, uint32_t lbo, uint32_t sbo, uint32_t mode) {
    return (uint64_t)((addr & 0x3FFFF) >> 4) | ((uint64_t)(lbo >> 4) << 16) | ((uint64_t)(sbo >> 4) << 32) | ((uint64_t)mode << 62);
}
template <int N> __device__ __forceinline__ void fence_regs(float (&r)[N]) {
#pragma unroll
    for (int i = 0; i < N; i++) asm volatile("" : "+f"(r[i])::"memory");
}
template <int N> __device__ __forceinline__ void fence_regs(uint32_t (&r)[N]) {
#pragma unroll
    for (int i = 0; i < N; i++) asm volatile("" : "+r"(r[i])::"memory");
}
__device__ __forceinline__ void mbar_init(uint32_t bar, uint32_t count) {
    asm volatile("mbarrier.init.shared::cta.b64 [%0], %1;" ::"r"(bar), "r"(count) : "memory");
}
__device__ __forceinline__ void mbar_expect_tx(uint32_t bar, uint32_t bytes) {
    asm volatile("mbarrier.arrive.expect_tx.shared::cta.b64 _, [%0], %1;" ::"r"(bar), "r"(bytes) : "memory");
}
__device__ __forceinline__ void mbar_arrive_cluster(uint32_t bar, uint32_t cta) {
    asm volatile("{\n.reg .b32 ra;\nmapa.shared::cluster.u32 ra, %0, %1;\n"
                 "mbarrier.arrive.shared::cluster.b64 _, [ra];\n}\n" ::"r"(bar), "r"(cta) : "memory");
}
__device__ __forceinline__ bool mbar_try(uint32_t bar, uint32_t parity) {
    uint32_t ok;
    asm volatile("{\n.reg .pred p;\nmbarrier.try_wait.parity.shared::cta.b64 p, [%1], %2;\nselp.u32 %0, 1, 0, p;\n}\n"
                 : "=r"(ok) : "r"(bar), "r"(parity) : "memory");
    return ok != 0;
}
__device__ __forceinline__ void mbar_wait(uint32_t bar, uint32_t parity) {
    if (mbar_try(bar, parity)) return;
#pragma unroll 1
    for (uint32_t i = 0; i < (1u << 22); i++)
        if (mbar_try(bar, parity)) return;
    __trap();
}
__device__ __forceinline__ void mbar_wait_warp(uint32_t bar, uint32_t parity) {
    if (__all_sync(~0u, mbar_try(bar, parity))) return;
#pragma unroll 1
    for (uint32_t i = 0; i < (1u << 22); i++)
        if (__all_sync(~0u, mbar_try(bar, parity))) return;
    __trap();
}
__device__ __forceinline__ void fence_async_smem() { asm volatile("fence.proxy.async.shared::cta;" ::: "memory"); }
__device__ __forceinline__ void tma_2d(uint32_t dst, const CUtensorMap* tm, int c0, int c1, uint32_t bar) {
    asm volatile("cp.async.bulk.tensor.2d.shared::cluster.global.mbarrier::complete_tx::bytes [%0], [%1, {%3, %4}], [%2];"
                 ::"r"(dst), "l"(tm), "r"(bar), "r"(c0), "r"(c1) : "memory");
}
__device__ __forceinline__ void tma_2d_mc(uint32_t dst, const CUtensorMap* tm, int c0, int c1, uint32_t bar, uint16_t mask) {
    asm volatile("cp.async.bulk.tensor.2d.shared::cluster.global.mbarrier::complete_tx::bytes.multicast::cluster [%0], [%1, {%3, %4}], [%2], %5;"
                 ::"r"(dst), "l"(tm), "r"(bar), "r"(c0), "r"(c1), "h"(mask) : "memory");
}
__device__ __forceinline__ void tma_3d(uint32_t dst, const CUtensorMap* tm, int c0, int c1, int c2, uint32_t bar) {
    asm volatile("cp.async.bulk.tensor.3d.shared::cluster.global.mbarrier::complete_tx::bytes [%0], [%1, {%3, %4, %5}], [%2];"
                 ::"r"(dst), "l"(tm), "r"(bar), "r"(c0), "r"(c1), "r"(c2) : "memory");
}
__device__ __forceinline__ void mbar_arrive(uint32_t bar) {
    asm volatile("mbarrier.arrive.shared::cta.b64 _, [%0];" ::"r"(bar) : "memory");
}
__device__ __forceinline__ void tma_4d(uint32_t dst, const CUtensorMap* tm, int c0, int c1, int c2, int c3, uint32_t bar) {
    asm volatile("cp.async.bulk.tensor.4d.shared::cluster.global.mbarrier::complete_tx::bytes [%0], [%1, {%3, %4, %5, %6}], [%2];"
                 ::"r"(dst), "l"(tm), "r"(bar), "r"(c0), "r"(c1), "r"(c2), "r"(c3) : "memory");
}
__device__ __forceinline__ void bulk_g2s(uint32_t dst, const void* src, uint32_t bytes, uint32_t bar) {
    asm volatile("cp.async.bulk.shared::cluster.global.mbarrier::complete_tx::bytes [%0], [%1], %2, [%3];"
                 ::"r"(dst), "l"(src), "r"(bytes), "r"(bar) : "memory");
}
__device__ __forceinline__ void bulk_s2g(void* dst, uint32_t src, uint32_t bytes) {
    asm volatile("cp.async.bulk.global.shared::cta.bulk_group [%0], [%1], %2;" ::"l"(dst), "r"(src), "r"(bytes) : "memory");
}
__device__ __forceinline__ void stmatrix_x4(uint32_t addr, uint32_t r0, uint32_t r1, uint32_t r2, uint32_t r3) {
    asm volatile("stmatrix.sync.aligned.m8n8.x4.shared.b16 [%0], {%1, %2, %3, %4};" ::"r"(addr), "r"(r0), "r"(r1), "r"(r2), "r"(r3) : "memory");
}
__device__ __forceinline__ float ex2(float x) { float y; asm("ex2.approx.ftz.f32 %0, %1;" : "=f"(y) : "f"(x)); return y; }
__device__ __forceinline__ uint32_t pack_bf16(float lo, float hi) {
    uint32_t r; asm("cvt.rn.bf16x2.f32 %0, %1, %2;" : "=r"(r) : "f"(hi), "f"(lo)); return r;
}

__device__ __forceinline__ void wgmma_ss_n96_tb(float (&d)[48], uint64_t da, uint64_t db) {
    asm volatile("wgmma.mma_async.sync.aligned.m64n96k16.f32.bf16.bf16 {"
        "%0, %1, %2, %3, %4, %5, %6, %7, %8, %9, %10, %11, %12, %13, %14, %15, "
        "%16, %17, %18, %19, %20, %21, %22, %23, %24, %25, %26, %27, %28, %29, %30, %31, "
        "%32, %33, %34, %35, %36, %37, %38, %39, %40, %41, %42, %43, %44, %45, %46, %47}, "
        "%48, %49, 1, 1, 1, 0, 1;\n"
        : "+f"(d[0]), "+f"(d[1]), "+f"(d[2]), "+f"(d[3]), "+f"(d[4]), "+f"(d[5]), "+f"(d[6]), "+f"(d[7]),
          "+f"(d[8]), "+f"(d[9]), "+f"(d[10]), "+f"(d[11]), "+f"(d[12]), "+f"(d[13]), "+f"(d[14]), "+f"(d[15]),
          "+f"(d[16]), "+f"(d[17]), "+f"(d[18]), "+f"(d[19]), "+f"(d[20]), "+f"(d[21]), "+f"(d[22]), "+f"(d[23]),
          "+f"(d[24]), "+f"(d[25]), "+f"(d[26]), "+f"(d[27]), "+f"(d[28]), "+f"(d[29]), "+f"(d[30]), "+f"(d[31]),
          "+f"(d[32]), "+f"(d[33]), "+f"(d[34]), "+f"(d[35]), "+f"(d[36]), "+f"(d[37]), "+f"(d[38]), "+f"(d[39]),
          "+f"(d[40]), "+f"(d[41]), "+f"(d[42]), "+f"(d[43]), "+f"(d[44]), "+f"(d[45]), "+f"(d[46]), "+f"(d[47])
        : "l"(da), "l"(db));
}
__device__ __forceinline__ void wgmma_ss_n96_tb_zero(float (&d)[48], uint64_t da, uint64_t db) {
    asm volatile("wgmma.mma_async.sync.aligned.m64n96k16.f32.bf16.bf16 {"
        "%0, %1, %2, %3, %4, %5, %6, %7, %8, %9, %10, %11, %12, %13, %14, %15, "
        "%16, %17, %18, %19, %20, %21, %22, %23, %24, %25, %26, %27, %28, %29, %30, %31, "
        "%32, %33, %34, %35, %36, %37, %38, %39, %40, %41, %42, %43, %44, %45, %46, %47}, "
        "%48, %49, 0, 1, 1, 0, 1;\n"
        : "=f"(d[0]), "=f"(d[1]), "=f"(d[2]), "=f"(d[3]), "=f"(d[4]), "=f"(d[5]), "=f"(d[6]), "=f"(d[7]),
          "=f"(d[8]), "=f"(d[9]), "=f"(d[10]), "=f"(d[11]), "=f"(d[12]), "=f"(d[13]), "=f"(d[14]), "=f"(d[15]),
          "=f"(d[16]), "=f"(d[17]), "=f"(d[18]), "=f"(d[19]), "=f"(d[20]), "=f"(d[21]), "=f"(d[22]), "=f"(d[23]),
          "=f"(d[24]), "=f"(d[25]), "=f"(d[26]), "=f"(d[27]), "=f"(d[28]), "=f"(d[29]), "=f"(d[30]), "=f"(d[31]),
          "=f"(d[32]), "=f"(d[33]), "=f"(d[34]), "=f"(d[35]), "=f"(d[36]), "=f"(d[37]), "=f"(d[38]), "=f"(d[39]),
          "=f"(d[40]), "=f"(d[41]), "=f"(d[42]), "=f"(d[43]), "=f"(d[44]), "=f"(d[45]), "=f"(d[46]), "=f"(d[47])
        : "l"(da), "l"(db));
}
__device__ __forceinline__ void wgmma_ss_n64_tb(float (&d)[32], uint64_t da, uint64_t db) {
    asm volatile("wgmma.mma_async.sync.aligned.m64n64k16.f32.bf16.bf16 {"
        "%0, %1, %2, %3, %4, %5, %6, %7, %8, %9, %10, %11, %12, %13, %14, %15, "
        "%16, %17, %18, %19, %20, %21, %22, %23, %24, %25, %26, %27, %28, %29, %30, %31}, "
        "%32, %33, 1, 1, 1, 0, 1;\n"
        : "+f"(d[0]), "+f"(d[1]), "+f"(d[2]), "+f"(d[3]), "+f"(d[4]), "+f"(d[5]), "+f"(d[6]), "+f"(d[7]),
          "+f"(d[8]), "+f"(d[9]), "+f"(d[10]), "+f"(d[11]), "+f"(d[12]), "+f"(d[13]), "+f"(d[14]), "+f"(d[15]),
          "+f"(d[16]), "+f"(d[17]), "+f"(d[18]), "+f"(d[19]), "+f"(d[20]), "+f"(d[21]), "+f"(d[22]), "+f"(d[23]),
          "+f"(d[24]), "+f"(d[25]), "+f"(d[26]), "+f"(d[27]), "+f"(d[28]), "+f"(d[29]), "+f"(d[30]), "+f"(d[31])
        : "l"(da), "l"(db));
}
template <uint32_t HI>
__device__ __forceinline__ void wgmma_rs_n64_zero(float (&d)[32], uint32_t a0, uint32_t a1, uint32_t a2, uint32_t a3, uint32_t db_lo) {
    asm volatile("{\n.reg .b64 dsc;\nmov.b64 dsc, {%36, %37};\n"
        "wgmma.mma_async.sync.aligned.m64n64k16.f32.bf16.bf16 {"
        "%0, %1, %2, %3, %4, %5, %6, %7, %8, %9, %10, %11, %12, %13, %14, %15, "
        "%16, %17, %18, %19, %20, %21, %22, %23, %24, %25, %26, %27, %28, %29, %30, %31}, "
        "{%32, %33, %34, %35}, dsc, 0, 1, 1, 0;\n}\n"
        : "+f"(d[0]), "+f"(d[1]), "+f"(d[2]), "+f"(d[3]), "+f"(d[4]), "+f"(d[5]), "+f"(d[6]), "+f"(d[7]),
          "+f"(d[8]), "+f"(d[9]), "+f"(d[10]), "+f"(d[11]), "+f"(d[12]), "+f"(d[13]), "+f"(d[14]), "+f"(d[15]),
          "+f"(d[16]), "+f"(d[17]), "+f"(d[18]), "+f"(d[19]), "+f"(d[20]), "+f"(d[21]), "+f"(d[22]), "+f"(d[23]),
          "+f"(d[24]), "+f"(d[25]), "+f"(d[26]), "+f"(d[27]), "+f"(d[28]), "+f"(d[29]), "+f"(d[30]), "+f"(d[31])
        : "r"(a0), "r"(a1), "r"(a2), "r"(a3), "r"(db_lo), "n"(HI));
}
__device__ __forceinline__ void wgmma_rs_n24_tb64(float (&d)[12], uint32_t a0, uint32_t a1, uint32_t a2, uint32_t a3, uint64_t db) {
    asm volatile("wgmma.mma_async.sync.aligned.m64n24k16.f32.bf16.bf16 {"
        "%0, %1, %2, %3, %4, %5, %6, %7, %8, %9, %10, %11}, "
        "{%12, %13, %14, %15}, %16, 1, 1, 1, 1;\n"
        : "+f"(d[0]), "+f"(d[1]), "+f"(d[2]), "+f"(d[3]), "+f"(d[4]), "+f"(d[5]), "+f"(d[6]), "+f"(d[7]),
          "+f"(d[8]), "+f"(d[9]), "+f"(d[10]), "+f"(d[11])
        : "r"(a0), "r"(a1), "r"(a2), "r"(a3), "l"(db));
}
__device__ __forceinline__ void wgmma_rs_n16_zero64(float (&d)[8], uint32_t a0, uint32_t a1, uint32_t a2, uint32_t a3, uint64_t db) {
    asm volatile("wgmma.mma_async.sync.aligned.m64n16k16.f32.bf16.bf16 {"
        "%0, %1, %2, %3, %4, %5, %6, %7}, "
        "{%8, %9, %10, %11}, %12, 0, 1, 1, 0;\n"
        : "+f"(d[0]), "+f"(d[1]), "+f"(d[2]), "+f"(d[3]), "+f"(d[4]), "+f"(d[5]), "+f"(d[6]), "+f"(d[7])
        : "r"(a0), "r"(a1), "r"(a2), "r"(a3), "l"(db));
}
__device__ __forceinline__ void wgmma_rs_n48_64(float (&d)[24], uint32_t a0, uint32_t a1, uint32_t a2, uint32_t a3, uint64_t db) {
    asm volatile("wgmma.mma_async.sync.aligned.m64n48k16.f32.bf16.bf16 {"
        "%0, %1, %2, %3, %4, %5, %6, %7, %8, %9, %10, %11, %12, %13, %14, %15, "
        "%16, %17, %18, %19, %20, %21, %22, %23}, "
        "{%24, %25, %26, %27}, %28, 1, 1, 1, 0;\n"
        : "+f"(d[0]), "+f"(d[1]), "+f"(d[2]), "+f"(d[3]), "+f"(d[4]), "+f"(d[5]), "+f"(d[6]), "+f"(d[7]),
          "+f"(d[8]), "+f"(d[9]), "+f"(d[10]), "+f"(d[11]), "+f"(d[12]), "+f"(d[13]), "+f"(d[14]), "+f"(d[15]),
          "+f"(d[16]), "+f"(d[17]), "+f"(d[18]), "+f"(d[19]), "+f"(d[20]), "+f"(d[21]), "+f"(d[22]), "+f"(d[23])
        : "r"(a0), "r"(a1), "r"(a2), "r"(a3), "l"(db));
}
template <uint32_t HI>
__device__ __forceinline__ void wgmma_rs_n24_tb(float (&d)[12], uint32_t a0, uint32_t a1, uint32_t a2, uint32_t a3, uint32_t db_lo) {
    asm volatile("{\n.reg .b64 dsc;\nmov.b64 dsc, {%16, %17};\n"
        "wgmma.mma_async.sync.aligned.m64n24k16.f32.bf16.bf16 {"
        "%0, %1, %2, %3, %4, %5, %6, %7, %8, %9, %10, %11}, "
        "{%12, %13, %14, %15}, dsc, 1, 1, 1, 1;\n}\n"
        : "+f"(d[0]), "+f"(d[1]), "+f"(d[2]), "+f"(d[3]), "+f"(d[4]), "+f"(d[5]), "+f"(d[6]), "+f"(d[7]),
          "+f"(d[8]), "+f"(d[9]), "+f"(d[10]), "+f"(d[11])
        : "r"(a0), "r"(a1), "r"(a2), "r"(a3), "r"(db_lo), "n"(HI));
}


constexpr int NSLOT = 4, NSTEP = 16;
__host__ __device__ constexpr int step_half(int t) { return t < 3 ? 0 : (t > 12 ? 1 : (t & 1)); }
__host__ __device__ constexpr int step_kb(int t) { return t < 3 ? t : (t > 12 ? t - 8 : ((t & 1) ? (t - 3) / 2 : (t + 2) / 2)); }
constexpr uint32_t XS_BYTES = 32768, WS_BYTES = 12288, WBUF = NSLOT * XS_BYTES;
constexpr uint32_t REC = 5120, RECD = REC / 16, KVA = 0, KVB = 32 * REC, BARS = 28 * 8192;
static_assert(KVB + 12 * REC <= BARS && KVB == 20 * 8192, "layout");
constexpr uint32_t FULL_BAR = BARS, EMPTY_BAR = BARS + 40, X_BAR = BARS + 80,
                   MISC = BARS + 96,
                   STATS = BARS + 128,
                   CONSTS = BARS + 192,
                   P3BAR = BARS + 320,
                   CP_BAR = P3BAR + 38 * 8,
                   KV_BAR = CP_BAR + 24,
                   W_BAR = KV_BAR + 16;
constexpr uint32_t SMEM1_BYTES = W_BAR + 64;
static_assert(WBUF + 8 * WS_BYTES <= BARS, "ring too large");

constexpr uint32_t KHI = (uint32_t)(make_desc(0, 1024, 128, 0) >> 32), VHI = (uint32_t)(make_desc(0, 128, 1024, 0) >> 32);
constexpr uint32_t dKA = (uint32_t)make_desc(SMEM_BASE + KVA, 1024, 128, 0), dVA = (uint32_t)make_desc(SMEM_BASE + KVA + 2048, 128, 1024, 0);
constexpr uint32_t dKB = (uint32_t)make_desc(SMEM_BASE + KVB, 1024, 128, 0), dVB = (uint32_t)make_desc(SMEM_BASE + KVB + 2048, 128, 1024, 0);

constexpr float QSCALE = 0.25f * 1.4426950408889634f;
constexpr float EXP_MAGIC = 381.401059f;

__device__ __forceinline__ uint32_t exp2_sw(float y0, float y1, uint32_t one2) {
    const uint32_t w = __byte_perm(__float_as_uint(y0), __float_as_uint(y1), 0x6521);
    uint32_t u, z;
    asm("lop3.b32 %0, %1, 0x007f007f, %2, 0xEA;" : "=r"(u) : "r"(w), "r"(one2));
    asm("fma.rn.bf16x2 %0, %1, %1, %2;" : "=r"(z) : "r"(u), "r"(0x40034003u));
    return w - u + z;
}

__device__ __forceinline__ void make_masks(uint32_t (&M)[9]) {
    uint32_t t;
    asm volatile("mov.u32 %0, %tid.x;" : "=r"(t));
    const int s0 = 16 - 16 * ((int)((t >> 1) & 48) + (int)((t >> 2) & 7) - 2 * (int)(t & 3));
    M[0] = 0; M[8] = 0xffffffffu;
#pragma unroll
    for (int i = 1; i < 8; i++) asm("shr.u32 %0, %1, %2;" : "=r"(M[i]) : "r"(0xffffffffu), "r"(max(s0 - 128 * (i - 7), 0)));
}

struct Scores { float m[8], p[24]; };

__device__ __forceinline__ void load_magic(Scores& S, int i, uint32_t caddr) {
    asm volatile("ld.volatile.shared.v4.f32 {%0, %1, %2, %3}, [%4];"
                 : "=f"(S.p[4 * i]), "=f"(S.p[4 * i + 1]), "=f"(S.p[4 * i + 2]), "=f"(S.p[4 * i + 3]) : "r"(caddr + 16 * i));
}
template <uint32_t HI> __device__ __forceinline__ uint64_t desc64(uint32_t lo) {
    uint64_t d;
    asm("mov.b64 %0, {%1, %2};" : "=l"(d) : "r"(lo), "n"(HI));
    return d;
}
__device__ __forceinline__ void issue_qk(Scores& S, const uint32_t (&q)[4], uint64_t kd64) {
    wgmma_rs_n16_zero64(S.m, q[0], q[1], q[2], q[3], kd64);
    wgmma_rs_n48_64(S.p, q[0], q[1], q[2], q[3], kd64 + 16);
}

template <int MODE, bool QK>
__device__ __forceinline__ void attn_step64(Scores& S, float (&O)[12], const uint32_t (&qn)[4], uint64_t kd_next, uint64_t vd64,
                                          uint32_t one2, uint32_t caddr) {
    uint32_t P[16], M[9];
    if (MODE) make_masks(M);
#pragma unroll
    for (int i = 0; i < 4; i++) P[i] = pack_bf16(ex2(S.m[2 * i]), ex2(S.m[2 * i + 1]));
#pragma unroll
    for (int i = 0; i < 6; i++) {
        P[4 + 2 * i] = exp2_sw(S.p[4 * i], S.p[4 * i + 1], one2);
        P[5 + 2 * i] = exp2_sw(S.p[4 * i + 2], S.p[4 * i + 3], one2);
        if (QK) load_magic(S, i, caddr);
    }
#pragma unroll
    for (int i = 0; i < 16; i++) {
        if (MODE == 1) P[i] &= M[(i & 1) - (i >> 1) + 7];
        if (MODE == 2) P[i] &= ~M[(i & 1) - (i >> 1) + 7];
    }
    fence_regs(P); fence_regs(S.p);
    wg_fence();
#pragma unroll
    for (int k = 0; k < 4; k++) wgmma_rs_n24_tb64(O, P[4 * k], P[4 * k + 1], P[4 * k + 2], P[4 * k + 3], vd64 + k * 16);
    if (QK) issue_qk(S, qn, kd_next);
    wg_commit();
    wg_wait<0>();
    fence_regs(S.m); fence_regs(S.p); fence_regs(P); fence_regs(O);
}

template <int MODE, bool QK>
__device__ __forceinline__ void attn_step(Scores& S, float (&O)[12], const uint32_t (&qn)[4], uint32_t kd_next, uint32_t vd,
                                          uint32_t one2, uint32_t caddr) {
    attn_step64<MODE, QK>(S, O, qn, desc64<KHI>(kd_next), desc64<VHI>(vd), one2, caddr);
}

template <int UNR>
__device__ __forceinline__ void attn_run(Scores& S, float (&O)[12], const uint32_t (&q)[4], uint32_t vd, int n, uint32_t one2, uint32_t caddr) {
#pragma unroll 1
    for (const uint32_t vend = vd + n * RECD; vd != vend; vd += UNR * RECD) {
        const uint64_t k64 = desc64<KHI>(vd + RECD + (dKA - dVA)), v64 = desc64<VHI>(vd);
#pragma unroll
        for (int u = 0; u < UNR; u++) attn_step64<0, true>(S, O, q, k64 + u * RECD, v64 + u * RECD, one2, caddr);
    }
}
__device__ __forceinline__ void zero_o(float (&O)[12]) {
#pragma unroll
    for (int i = 0; i < 12; i++) O[i] = 0.f;
    fence_regs(O);
}

__device__ __forceinline__ void attn_slow(float (&O)[12], const uint32_t (&q)[4], uint32_t kd, uint32_t vd,
                                          int ntiles, bool mask_first, bool mask_last) {
    const int lane = threadIdx.x & 31;
    const int dbase = ((threadIdx.x >> 5) & 3) * 16 + (lane >> 2) - 2 * (lane & 3);
    uint32_t P[16];
    float S[32];
    float m0 = -INFINITY, m1 = -INFINITY;
#pragma unroll
    for (int i = 0; i < 32; i++) S[i] = 0.f;
#pragma unroll
    for (int i = 0; i < 12; i++) O[i] = 0.f;
#pragma unroll 1
    for (int j = 0; j < ntiles; j++) {
        fence_regs(S);
        wg_fence();
        wgmma_rs_n64_zero<KHI>(S, q[0], q[1], q[2], q[3], kd + j * RECD);
        wg_commit();
        wg_wait<0>();
        fence_regs(S);
        const bool mf = mask_first && j == 0, ml = mask_last && j == ntiles - 1;
        if (mf || ml) {
#pragma unroll
            for (int i = 0; i < 32; i++) {
                const int d = dbase + 8 * ((i >> 1) & 1) - 8 * (i >> 2) - (i & 1);
                const bool keep = ml ? (d >= 0) : (d < 0);
                if (!keep) S[i] = -1e9f * 1.4426950408889634f;
            }
        }
        float x0 = m0, x1 = m1;
#pragma unroll
        for (int b = 0; b < 8; b++) {
            x0 = fmaxf(x0, fmaxf(S[4 * b], S[4 * b + 1]));
            x1 = fmaxf(x1, fmaxf(S[4 * b + 2], S[4 * b + 3]));
        }
        x0 = fmaxf(x0, __shfl_xor_sync(~0u, x0, 1)); x0 = fmaxf(x0, __shfl_xor_sync(~0u, x0, 2));
        x1 = fmaxf(x1, __shfl_xor_sync(~0u, x1, 1)); x1 = fmaxf(x1, __shfl_xor_sync(~0u, x1, 2));
        const float a0 = ex2(m0 - x0), a1 = ex2(m1 - x1);
        m0 = x0; m1 = x1;
#pragma unroll
        for (int b = 0; b < 3; b++) { O[4 * b] *= a0; O[4 * b + 1] *= a0; O[4 * b + 2] *= a1; O[4 * b + 3] *= a1; }
#pragma unroll
        for (int b = 0; b < 8; b++) {
            P[2 * b] = pack_bf16(ex2(S[4 * b] - m0), ex2(S[4 * b + 1] - m0));
            P[2 * b + 1] = pack_bf16(ex2(S[4 * b + 2] - m1), ex2(S[4 * b + 3] - m1));
        }
        fence_regs(P); fence_regs(O);
        wg_fence();
#pragma unroll
        for (int k = 0; k < 4; k++) wgmma_rs_n24_tb<VHI>(O, P[4 * k], P[4 * k + 1], P[4 * k + 2], P[4 * k + 3], vd + j * RECD + k * 16);
        wg_commit();
        wg_wait<0>();
        fence_regs(P); fence_regs(O);
    }
}

__device__ __forceinline__ bool shift_free_ok(float q2, float k2, float vlo, float vhi) {
    float b;
    asm("sqrt.approx.f32 %0, %1;" : "=f"(b) : "f"(q2 * k2));
    b = b * 1.02f + 1.f;
    const float e = ex2(b);
    return __all_sync(~0u, b <= 110.f && vhi * e <= 0x1p114f && vlo * 0x1p99f >= e);
}

__device__ __forceinline__ void store_o(const float (&O)[12], __nv_bfloat16* dst) {
    float i0, i1;
    asm("rcp.approx.ftz.f32 %0, %1;" : "=f"(i0) : "f"(O[8]));
    asm("rcp.approx.ftz.f32 %0, %1;" : "=f"(i1) : "f"(O[10]));
    const uint32_t a0 = pack_bf16(O[0] * i0, O[1] * i0), a1 = pack_bf16(O[4] * i0, O[5] * i0);
    const uint32_t a2 = pack_bf16(O[2] * i1, O[3] * i1), a3 = pack_bf16(O[6] * i1, O[7] * i1);
    const bool o1 = threadIdx.x & 1, o2 = threadIdx.x & 2;
    const uint32_t x0 = __shfl_xor_sync(~0u, o1 ? a0 : a1, 1), x1 = __shfl_xor_sync(~0u, o1 ? a2 : a3, 1);
    const uint32_t b0 = o1 ? x0 : a0, b1 = o1 ? a1 : x0, b2 = o1 ? x1 : a2, b3 = o1 ? a3 : x1;
    const uint32_t y0 = __shfl_xor_sync(~0u, o2 ? b0 : b2, 2), y1 = __shfl_xor_sync(~0u, o2 ? b1 : b3, 2);
    *reinterpret_cast<uint4*>(dst) = o2 ? make_uint4(y0, y1, b2, b3) : make_uint4(b0, b1, y0, y1);
}

__device__ __forceinline__ uint32_t absmax2(uint32_t a, uint32_t b) {
    uint32_t m;
    asm("max.NaN.xorsign.abs.bf16x2 %0, %1, %2;" : "=r"(m) : "r"(a), "r"(b));
    return m;
}
__device__ __forceinline__ uint32_t absmax4(const uint32_t* a) { return absmax2(absmax2(a[0], a[1]), absmax2(a[2], a[3])); }
__device__ __forceinline__ uint32_t absmax_warp(uint32_t a, uint32_t b) {
    const uint32_t m = absmax2(a, b);
    return __reduce_max_sync(~0u, max(m & 0x7fff0000u, (m << 16) & 0x7fff0000u));
}
__device__ __forceinline__ uint32_t up16(uint32_t fbits) { return min(fbits >> 16, 0x7ffeu) + 1u; }

__device__ __forceinline__ void cnt_release(uint32_t* p, uint32_t n) { asm volatile("red.release.gpu.global.add.u32 [%0], %1;" ::"l"(p), "r"(n) : "memory"); }
__device__ __forceinline__ void cnt_wait_warp(const uint32_t* p, uint32_t target) {
#pragma unroll 1
    for (uint32_t i = 0; i < (1u << 22); i++) {
        uint32_t v;
        asm volatile("ld.relaxed.gpu.global.u32 %0, [%1];" : "=r"(v) : "l"(p) : "memory");
        if (__all_sync(~0u, ((v ^ target) & 0xfffffu) == 0)) { asm volatile("fence.acquire.gpu;" ::: "memory"); return; }
    }
    __trap();
}

__device__ __forceinline__ void row_norm_part(const float (&a)[48], int i, float& s0, float& s1) {
    const float* p = a + 24 * (i >> 1) + 8 * (i & 1);
    s0 = (p[0] * p[0] + p[1] * p[1]) + (p[4] * p[4] + p[5] * p[5]);
    s1 = (p[2] * p[2] + p[3] * p[3]) + (p[6] * p[6] + p[7] * p[7]);
}
__device__ __forceinline__ void row_norm_stats(const float (&s)[4][4], int lane, uint32_t stats_addr) {
    float t[4][2];
    const bool o1 = lane & 1, o2 = lane & 2;
#pragma unroll
    for (int i = 0; i < 4; i++) {
        t[i][0] = (o1 ? s[i][1] : s[i][0]) + __shfl_xor_sync(~0u, o1 ? s[i][0] : s[i][1], 1);
        t[i][1] = (o1 ? s[i][3] : s[i][2]) + __shfl_xor_sync(~0u, o1 ? s[i][2] : s[i][3], 1);
    }
    uint32_t m[4];
#pragma unroll
    for (int i = 0; i < 4; i++) {
        const float v = (o2 ? t[i][1] : t[i][0]) + __shfl_xor_sync(~0u, o2 ? t[i][0] : t[i][1], 2);
        m[i] = __float_as_uint(v);
    }
#pragma unroll
    for (int i = 0; i < 4; i++) m[i] = __reduce_max_sync(~0u, m[i]);
    const uint32_t mv = o2 ? (o1 ? m[3] : m[2]) : (o1 ? m[1] : m[0]);
    if (lane < 4) asm volatile("red.shared.max.u32 [%0], %1;" ::"r"(stats_addr + 4 * lane), "r"(mv) : "memory");
}
__device__ __forceinline__ void finish_branch(float (&a)[48], int br, float (&s)[4][4], int mt, uint32_t (&q)[4], uint32_t (&kv)[16]) {
#pragma unroll
    for (int i = 0; i < 8; i++) a[24 * br + i] *= QSCALE;
    row_norm_part(a, 2 * br, s[2 * br][2 * mt], s[2 * br][2 * mt + 1]);
    row_norm_part(a, 2 * br + 1, s[2 * br + 1][2 * mt], s[2 * br + 1][2 * mt + 1]);
#pragma unroll
    for (int i = 0; i < 4; i++) q[i] = pack_bf16(a[24 * br + 2 * i], a[24 * br + 2 * i + 1]);
#pragma unroll
    for (int i = 0; i < 8; i++) kv[8 * br + i] = pack_bf16(a[24 * br + 8 + 2 * i], a[24 * br + 8 + 2 * i + 1]);
}

__global__ void __launch_bounds__(512, 1)
fused_kernel(const __grid_constant__ CUtensorMap tm_x, const __grid_constant__ CUtensorMap tm_wa,
             const __grid_constant__ CUtensorMap tm_wb,
             const __grid_constant__ CUtensorMap tm_woa4, const __grid_constant__ CUtensorMap tm_wob4,
             const __grid_constant__ CUtensorMap tm_o1, const __grid_constant__ CUtensorMap tm_o4,
             const __nv_bfloat16* __restrict__ x, const __nv_bfloat16* __restrict__ gate_w, __nv_bfloat16* __restrict__ out) {
    extern __shared__ __align__(1024) uint8_t sp[];
    const uint32_t sb = smem_u32(sp);
    if ((sb & 0x3FFFF) != SMEM_BASE) __trap();
    const int tid = threadIdx.x, lane = tid & 31;
    const int warp = __shfl_sync(~0u, tid >> 5, 0), wg = warp >> 2, w4 = warp & 3;
    const int bid = blockIdx.x, rank = bid & 1, qb = (bid >> 1) & 3, head = ((bid >> 3) << 1) | rank;
    const int slot = head * 4 + qb;

    if (tid == 128) {
        asm volatile("prefetch.tensormap [%0];" ::"l"(&tm_wa) : "memory");
        asm volatile("prefetch.tensormap [%0];" ::"l"(&tm_wb) : "memory");
    }
    if (tid == 0) {
        for (int s = 0; s < NSLOT; s++) mbar_init(sb + FULL_BAR + 8 * s, 1);
        for (int s = 0; s < 3; s++) mbar_init(sb + W_BAR + 8 * s, 1);
        asm volatile("fence.mbarrier_init.release.cluster;" ::: "memory");
        for (int t = 0; t < 4; t++) {
            mbar_expect_tx(sb + FULL_BAR + 8 * t, XS_BYTES);
            tma_2d(sb + t * XS_BYTES, &tm_x, step_kb(t) * 64, qb * 512 + step_half(t) * 256, sb + FULL_BAR + 8 * t);
            if (t < 3) {
                mbar_expect_tx(sb + W_BAR + 8 * t, WS_BYTES);
                tma_4d(sb + WBUF + (7 - t) * WS_BYTES, &tm_wa, 0, t * 64, head, 0, sb + W_BAR + 8 * t);
                tma_4d(sb + WBUF + (7 - t) * WS_BYTES + 6144, &tm_wb, 0, t * 64, head, 0, sb + W_BAR + 8 * t);
            }
        }
    }
    if (tid == 256) {
        for (int s = 0; s < NSLOT; s++) mbar_init(sb + EMPTY_BAR + 8 * s, 8);
        for (int s = 3; s < 8; s++) mbar_init(sb + W_BAR + 8 * s, 1);
        mbar_init(sb + X_BAR, 1);
        mbar_init(sb + X_BAR + 8, 2);
        asm volatile("fence.mbarrier_init.release.cluster;" ::: "memory");
    }
    if (tid >= 32 && tid < 48) {
        if (tid != 37) reinterpret_cast<uint32_t*>(sp + MISC)[tid - 32] = tid == 36 ? 0xbf80bf80u : 0u;
    }
    if (tid >= 64 && tid < 88) reinterpret_cast<float*>(sp + CONSTS)[tid - 64] = EXP_MAGIC;
    __syncthreads();
    asm volatile("barrier.cluster.arrive.relaxed.aligned;" ::: "memory");

    uint32_t qa0[4], qa1[4], qb0[4], qb1[4];
    uint4* const qs = g_qsave + bid * 3584 + tid;
    const uint32_t caddr = sb + CONSTS;
    Scores S;
    {
        float acc0[48], acc1[48], nrm[4][4];
        uint32_t kv0[16], kv1[16], vmx[2];
        uint4 gx[2], gw[2];
        uint32_t cnt0;
        const int grow = qb * 512 + head * 16 + warp;
#pragma unroll
        for (int c = 0; c < 2; c++) {
            gx[c] = __ldg(reinterpret_cast<const uint4*>(x + (size_t)grow * DM) + lane + 32 * c);
            gw[c] = __ldg(reinterpret_cast<const uint4*>(gate_w) + lane + 32 * c);
        }
        asm volatile("ld.relaxed.gpu.global.u32 %0, [%1];" : "=r"(cnt0) : "l"(&g_cnt[1][qb * 32]) : "memory");
        const uint32_t ra = sb + KVA + wg * REC + (w4 * 16 + (lane & 15)) * 16 + (lane >> 4) * 1024, rb = ra + (KVB + 4 * REC - KVA);
        const uint64_t da0 = make_desc(SMEM_BASE + wg * 8192, 16, 1024, 1);
        constexpr uint64_t db0 = make_desc(SMEM_BASE + WBUF, 2048, 256, 3);
#pragma unroll
        for (int t = 0; t < NSTEP; t++) {
            const int s = t % NSLOT, hf = step_half(t), kb = step_kb(t);
            if (hf == 0) mbar_wait_warp(sb + W_BAR + 8 * kb, 0);
            mbar_wait_warp(sb + FULL_BAR + 8 * s, (t / NSLOT) & 1);
            const uint64_t da = da0 + (uint64_t)(s * (XS_BYTES >> 4)), db = db0 + (uint64_t)((7 - kb) * (WS_BYTES >> 4));
            wg_fence();
#pragma unroll
            for (int k = 0; k < 4; k++) {
                if (kb == 0 && k == 0) wgmma_ss_n96_tb_zero(hf ? acc1 : acc0, da, db);
                else wgmma_ss_n96_tb(hf ? acc1 : acc0, da + 2 * k, db + 32 * k);
            }
            wg_commit();
            if (t >= 1 && t <= 14) wg_wait<1>();
            if (t >= 1 && t - 1 + NSLOT < NSTEP) {
                const int ps = (t - 1) % NSLOT, nt = t - 1 + NSLOT;
                if (w4 == 3 && lane == 0) mbar_arrive_cluster(sb + EMPTY_BAR + 8 * ps, nt & 1);
                if (tid == 0 && step_half(nt) == 0) {
                    const int nk = step_kb(nt);
                    mbar_expect_tx(sb + W_BAR + 8 * nk, WS_BYTES);
                    tma_4d(sb + WBUF + (7 - nk) * WS_BYTES, &tm_wa, 0, nk * 64, head, 0, sb + W_BAR + 8 * nk);
                    tma_4d(sb + WBUF + (7 - nk) * WS_BYTES + 6144, &tm_wb, 0, nk * 64, head, 0, sb + W_BAR + 8 * nk);
                }
                __syncwarp();
                if (warp == 0 && (nt & 1) == rank) mbar_wait_warp(sb + EMPTY_BAR + 8 * ps, ((t - 1) / NSLOT) & 1);
                if (tid == 0) {
                    mbar_expect_tx(sb + FULL_BAR + 8 * ps, XS_BYTES);
                    if ((nt & 1) == rank)
                        tma_2d_mc(sb + ps * XS_BYTES, &tm_x, step_kb(nt) * 64, qb * 512 + step_half(nt) * 256, sb + FULL_BAR + 8 * ps, 3);
                }
                __syncwarp();
            }
            if (t == 0) asm volatile("barrier.cluster.wait.aligned;" ::: "memory");
            if (t == 1) {
                float ga = 0.f, gb = 0.f;
#pragma unroll
                for (int c = 0; c < 2; c++) {
                    const uint32_t av[4] = {gx[c].x, gx[c].y, gx[c].z, gx[c].w}, gv[4] = {gw[c].x, gw[c].y, gw[c].z, gw[c].w};
#pragma unroll
                    for (int i = 0; i < 4; i++) {
                        ga += __uint_as_float(av[i] << 16) * __uint_as_float(gv[i] << 16);
                        gb += __uint_as_float(av[i] & 0xffff0000u) * __uint_as_float(gv[i] & 0xffff0000u);
                    }
                }
                gx[0].x = __float_as_uint(ga + gb);
            }
            if (t == 2) {
                float ga = __uint_as_float(gx[0].x);
#pragma unroll
                for (int o = 16; o; o >>= 1) ga += __shfl_xor_sync(~0u, ga, o);
                if (lane == 0) g_gate[grow] = __fdividef(1.f, 1.f + __expf(-ga));
                if (tid == 37) reinterpret_cast<uint32_t*>(sp + MISC)[5] = cnt0;
            }
            if (t >= 4 && t < 8 && tid == 128 * (t - 4) + 32) {
#pragma unroll
                for (int i = 11 * (t - 4); i < 11 * (t - 3) && i < 43; i++) mbar_init(sb + P3BAR + 8 * i, i >= 41 ? 16 : (i >= 38 ? 4 : (i >= 30 ? 2 : 1)));
            }
            if (t == 13) {
                fence_regs(acc0);
                finish_branch(acc0, 1, nrm, 0, qb0, kv0);
                qs[2 * 512] = make_uint4(qb0[0], qb0[1], qb0[2], qb0[3]);
            }
            if (t == 14) {
                finish_branch(acc0, 0, nrm, 0, qa0, kv0);
            }
            if (t == 15) {
                __syncthreads();
                stmatrix_x4(ra, kv0[0], kv0[1], kv0[2], kv0[3]);
                stmatrix_x4(ra + 2048, kv0[4], kv0[5], kv0[6], kv0[7]);
                stmatrix_x4(rb, kv0[8], kv0[9], kv0[10], kv0[11]);
                stmatrix_x4(rb + 2048, kv0[12], kv0[13], kv0[14], kv0[15]);
                uint8_t* const op = sp + KVA + (wg + ((tid >> 4) & 4)) * REC + 4096 + (tid & 63) * 16;
                *reinterpret_cast<uint4*>(op) = make_uint4(0x3f803f80u, 0x3f803f80u, 0x3f803f80u, 0x3f803f80u);
                *reinterpret_cast<uint4*>(op + (KVB + 4 * REC - KVA)) = make_uint4(0x3f803f80u, 0x3f803f80u, 0x3f803f80u, 0x3f803f80u);
                vmx[0] = absmax4(kv0 + 4); vmx[1] = absmax4(kv0 + 12);
                fence_async_smem();
                asm volatile("bar.sync %0, 128;" ::"r"(wg + 1) : "memory");
            }
        }
        wg_wait<0>();
        fence_regs(acc1);
        finish_branch(acc1, 1, nrm, 1, qb1, kv1);
        finish_branch(acc1, 0, nrm, 1, qa1, kv1);
        fence_regs(kv1); fence_regs(qa1); fence_regs(nrm[0]); fence_regs(nrm[1]); fence_regs(nrm[2]); fence_regs(nrm[3]);
#pragma unroll
        for (int i = 0; i < 8; i++) S.m[i] = 0.f;
#pragma unroll
        for (int i = 0; i < 6; i++) load_magic(S, i, caddr);
        fence_regs(S.m); fence_regs(S.p);
        wg_fence();
        issue_qk(S, qb1, desc64<KHI>(dKB + (wg + 4) * RECD));
        wg_commit();
        stmatrix_x4(rb + 4 * REC, kv1[8], kv1[9], kv1[10], kv1[11]);
        stmatrix_x4(rb + 4 * REC + 2048, kv1[12], kv1[13], kv1[14], kv1[15]);
        stmatrix_x4(ra + 4 * REC, kv1[0], kv1[1], kv1[2], kv1[3]);
        stmatrix_x4(ra + 4 * REC + 2048, kv1[4], kv1[5], kv1[6], kv1[7]);
        fence_async_smem();
        __syncwarp();
        if (lane == 0) mbar_arrive(sb + KV_BAR);
        row_norm_stats(nrm, lane, sb + STATS);
        {
            const uint32_t va = absmax_warp(vmx[0], absmax4(kv1 + 4)), vb = absmax_warp(vmx[1], absmax4(kv1 + 12));
            if (lane < 2) asm volatile("red.shared.max.u32 [%0], %1;" ::"r"(sb + STATS + 16 + 4 * lane), "r"(lane ? vb : va) : "memory");
        }
        __syncwarp();
        if (lane == 0) mbar_arrive(sb + KV_BAR + 8);
        wg_wait<0>();
        fence_regs(S.m); fence_regs(S.p);
        mbar_wait_warp(sb + KV_BAR, 0);
    }
    if (tid == 384) {
        uint8_t* dst = g_kv + (size_t)slot * 61440;
        bulk_s2g(dst, sb + KVA, 8 * REC);
        bulk_s2g(dst + 8 * REC, sb + KVB + 8 * REC, 4 * REC);
        asm volatile("cp.async.bulk.commit_group;" ::: "memory");
    }
    __syncwarp();

    const uint32_t one2 = *reinterpret_cast<volatile uint32_t*>(sp + MISC + 16);
    const float* st = reinterpret_cast<const float*>(sp + STATS);
    __nv_bfloat16* const obase = g_ocat + (size_t)(qb * 512 + wg * 64 + w4 * 16 + (lane >> 2) + (lane & 2) * 4) * 1024 + head * 16 + 8 * (lane & 1);
    float O[12];
    auto load_q = [&](uint32_t (&q)[4], int job) {
        asm volatile("ld.global.v4.u32 {%0, %1, %2, %3}, [%4];" : "=r"(q[0]), "=r"(q[1]), "=r"(q[2]), "=r"(q[3]) : "l"(qs + job * 512) : "memory");
    };
    const uint32_t* const stu = reinterpret_cast<const uint32_t*>(sp + STATS);
    auto cnt_target = [&]() { return *reinterpret_cast<const uint32_t*>(sp + MISC + 20) + 32u; };
    const int rowE = qb * 512 + 256 + (head >> 3) * 64, rowL = rowE - 256, n0 = (head & 7) * 64;
    auto p3_load_w = [&](int g) {
        mbar_expect_tx(sb + P3BAR + 8 * g, 32768);
        tma_2d(sb + (g == 0 ? 0 : g == 3 ? 4 : 16 + 4 * g) * 8192, g < 2 ? &tm_wob4 : &tm_woa4, n0, (g & 1) * 256, sb + P3BAR + 8 * g);
    };
    auto p3_load_o = [&](int late) {
        mbar_expect_tx(sb + P3BAR + 8 * (4 + late), 32768);
        tma_3d(sb + (8 + 4 * late) * 8192, &tm_o4, 0, late ? rowL : rowE, 8, sb + P3BAR + 8 * (4 + late));
    };
    auto save_q = [&](const uint32_t (&q)[4], int job) { qs[job * 512] = make_uint4(q[0], q[1], q[2], q[3]); };
    zero_o(O);
    if (__all_sync(~0u, one2 != 0))
        attn_step<2, true>(S, O, qb1, dKB + (wg + 5) * RECD, dVB + (wg + 4) * RECD, one2, caddr);
    mbar_wait_warp(sb + KV_BAR + 8, 0);
    const bool fast = shift_free_ok(st[0], st[1], st[4], st[4]) & shift_free_ok(st[2], st[3], st[5], st[5]);
    uint32_t redo = fast ? 0 : 15;
    {
        const uint32_t vd = dVB + (wg + 4) * RECD;
        if (fast) {
            attn_run<1>(S, O, qb1, vd + RECD, 3, one2, caddr);
        }
        if (tid == 384) {
            const unsigned long long fv = ((unsigned long long)((cnt_target() << 11) | up16(max(stu[4], stu[5]))) << 32) | (up16(stu[3]) << 16) | up16(stu[1]);
            asm volatile("cp.async.bulk.wait_group 0;" ::: "memory");
            asm volatile("st.relaxed.gpu.global.u64 [%0], %1;" ::"l"(g_flag + slot), "l"(fv) : "memory");
        }
        __syncwarp();
        if (!fast) save_q(qb1, 3);
        if (fast) {
            attn_step<1, true>(S, O, qa0, dKA, vd + 4 * RECD, one2, caddr);
            store_o(O, obase + 256 * 1024 + 512);
        }
    }
    {
        const int os = head * 4 + ((qb + wg + 1) & 3);
        const bool fetcher = w4 == 0 && wg < 3;
        auto poll = [&]() -> unsigned long long {
            unsigned long long f;
            asm volatile("ld.relaxed.gpu.global.u64 %0, [%1];" : "=l"(f) : "l"(g_flag + os) : "memory");
            return f;
        };
        if (fast) {
            zero_o(O);
            attn_step<0, true>(S, O, qa0, dKA + RECD, dVA, one2, caddr);
            attn_step<0, true>(S, O, qa0, dKA + 2 * RECD, dVA + RECD, one2, caddr);
        }
        unsigned long long f = 0;
        if (fetcher) f = poll();
        if (fast) {
            attn_step<0, true>(S, O, qa0, dKA + 3 * RECD, dVA + 2 * RECD, one2, caddr);
            attn_step<0, true>(S, O, qa0, dKA + 4 * RECD, dVA + 3 * RECD, one2, caddr);
        }
        if (fetcher) {
            const uint32_t tag = (cnt_target() >> 5) & 0xffffu;
#pragma unroll 1
            for (uint32_t i = 0; !__all_sync(~0u, (uint32_t)(f >> 48) == tag); i++) {
                if (i == (1u << 22)) __trap();
                f = poll();
            }
        }
        if (fetcher && lane == 0) {
            asm volatile("fence.acquire.gpu;" ::: "memory");
            asm volatile("fence.proxy.async.global;" ::: "memory");
            const bool halo = wg == 2 && qb > 0;
            *reinterpret_cast<unsigned long long*>(sp + STATS + 32 + wg * 8) = f;
            const uint32_t xb = sb + X_BAR + (wg ? 8 : 0);
            mbar_expect_tx(xb, halo ? 12 * REC : 8 * REC);
            const uint8_t* src = g_kv + (size_t)os * 61440;
            bulk_g2s(sb + KVA + (wg + 1) * 8 * REC, src, 8 * REC, xb);
            if (halo) bulk_g2s(sb + KVB, src + 8 * REC, 4 * REC, xb);
        }
        __syncwarp();
        if (fast) {
            attn_step<0, true>(S, O, qa0, dKA + 5 * RECD, dVA + 4 * RECD, one2, caddr);
            attn_step<0, true>(S, O, qa0, dKA + 6 * RECD, dVA + 5 * RECD, one2, caddr);
            attn_step<0, true>(S, O, qa0, dKA + 7 * RECD, dVA + 6 * RECD, one2, caddr);
            attn_step<0, true>(S, O, qa1, dKA, dVA + 7 * RECD, one2, caddr);
#pragma unroll
            for (int i = 0; i < 3; i++)
                qs[(4 + i) * 512] = make_uint4(__float_as_uint(O[4 * i]), __float_as_uint(O[4 * i + 1]), __float_as_uint(O[4 * i + 2]), __float_as_uint(O[4 * i + 3]));
        }
    }
    save_q(qa0, 0);
    const int first = qb > 0 ? 0 : 4 - wg;
    {
        if (fast) {
            zero_o(O);
            attn_run<2>(S, O, qa1, dVA, 6, one2, caddr);
        }
        mbar_wait_warp(sb + X_BAR, 0);
        if (fast) attn_run<2>(S, O, qa1, dVA + 6 * RECD, 8, one2, caddr);
        mbar_wait_warp(sb + X_BAR + 8, 0);
        {
            const uint32_t ka = max(stu[1], max(stu[8] << 16, max(stu[10] << 16, stu[12] << 16)));
            const uint32_t va = max(stu[4], max(stu[9] << 16, max(stu[11] << 16, stu[13] << 16)));
            if (!shift_free_ok(st[0], __uint_as_float(ka), st[4], __uint_as_float(va))) redo |= 3;
            if (!shift_free_ok(st[2], __uint_as_float(max(stu[3], stu[12] & 0xffff0000u)), st[5], __uint_as_float(max(stu[5], stu[13] << 16)))) redo |= 4;
        }
        if (redo) save_q(qa1, 1);
        if (fast) {
            attn_run<2>(S, O, qa1, dVA + 14 * RECD, 16, one2, caddr);
            load_q(qb0, 2);
            attn_step<0, true>(S, O, qa1, dKA + 31 * RECD, dVA + 30 * RECD, one2, caddr);
            attn_step<0, true>(S, O, qb0, dKB + (wg + first) * RECD, dVA + 31 * RECD, one2, caddr);
            store_o(O, obase + 256 * 1024);
        }
    }
    if (fast) {
        uint32_t vd = dVB + (wg + first) * RECD;
        zero_o(O);
        if (qb > 0) { attn_step<2, true>(S, O, qb0, vd + RECD + (dKA - dVA), vd, one2, caddr); vd += RECD; }
        load_q(qa0, 0);
        attn_run<1>(S, O, qb0, vd, qb > 0 ? 3 : wg, one2, caddr);
        attn_step<1, true>(S, O, qa0, dKA + 8 * RECD, dVB + (wg + 4) * RECD, one2, caddr);
        store_o(O, obase + 512);
    }
    const bool pf = !redo;
    if (pf) asm volatile("bar.arrive 7, 544;" ::: "memory");
    auto checkpoint = [&](int i) { if (pf && w4 == 3 && lane == 0) mbar_arrive(sb + CP_BAR + 8 * i); };
    if (fast) {
#pragma unroll
        for (int i = 0; i < 3; i++)
            asm volatile("ld.global.v4.f32 {%0, %1, %2, %3}, [%4];" : "=f"(O[4 * i]), "=f"(O[4 * i + 1]), "=f"(O[4 * i + 2]), "=f"(O[4 * i + 3]) : "l"(qs + (4 + i) * 512) : "memory");
        attn_run<2>(S, O, qa0, dVA + 8 * RECD, 6, one2, caddr);
        checkpoint(0);
        if (pf && warp == 15) {
            asm volatile("bar.sync 7, 544;" ::: "memory");
            if (lane == 0) cnt_release(&g_cnt[0][qb * 32], 1);
            __syncwarp();
        }
        attn_run<2>(S, O, qa0, dVA + 14 * RECD, 8, one2, caddr);
        if (pf && warp == 11) {
            mbar_wait_warp(sb + CP_BAR, 0);
            if (lane == 0) { p3_load_w(0); p3_load_w(1); p3_load_w(2); p3_load_w(3); }
            __syncwarp();
        }
        if (pf && warp == 7) cnt_wait_warp(&g_cnt[0][qb * 32], cnt_target());
        checkpoint(1);
        attn_run<2>(S, O, qa0, dVA + 22 * RECD, 6, one2, caddr);
        checkpoint(2);
        if (pf && warp == 11) {
            mbar_wait_warp(sb + CP_BAR + 8, 0);
            if (lane == 0) { asm volatile("fence.proxy.async.global;" ::: "memory"); p3_load_o(0); }
            __syncwarp();
        }
        attn_step<0, true>(S, O, qa0, dKA + 29 * RECD, dVA + 28 * RECD, one2, caddr);
        attn_step<0, true>(S, O, qa0, dKA + 30 * RECD, dVA + 29 * RECD, one2, caddr);
        if (pf && warp == 15) {
            mbar_wait_warp(sb + CP_BAR + 16, 0);
            if (lane == 0) { asm volatile("fence.proxy.async.global;" ::: "memory"); p3_load_o(1); }
            __syncwarp();
        }
        attn_step<0, true>(S, O, qa0, dKA + 31 * RECD, dVA + 30 * RECD, one2, caddr);
        attn_step<0, false>(S, O, qa0, 0, dVA + 31 * RECD, one2, caddr);
        store_o(O, obase);
    }
#pragma unroll 1
    for (int job = 0; redo >> job; job++) {
        if (!((redo >> job) & 1)) continue;
        const uint4 qv = qs[job * 512];
        const uint32_t q[4] = {qv.x, qv.y, qv.z, qv.w};
        const int f0 = job == 2 ? first : 0;
        const uint32_t off = (wg + (job & 1) * 4 + f0) * RECD;
        const bool isb = job >= 2;
        attn_slow(O, q, isb ? dKB + off : dKA, isb ? dVB + off : dVA, isb ? 5 - f0 : 32, isb && f0 == 0, isb);
        store_o(O, obase + (job & 1) * 256 * 1024 + (isb ? 512 : 0));
    }
    __syncthreads();

    if (wg >= 2) {
        if (warp == 12) {
            if (lane == 0) {
                if (redo) cnt_release(&g_cnt[0][qb * 32], 1);
                cnt_release(&g_cnt[1][qb * 32], 1);
            }
            __syncwarp();
            cnt_wait_warp(&g_cnt[1][qb * 32], cnt_target());
            if (lane == 0) {
                asm volatile("fence.proxy.async.global;" ::: "memory");
#pragma unroll 1
                for (int i = 0; i < 8; i++) {
                    mbar_wait(sb + P3BAR + 8 * (30 + i), 0);
                    mbar_expect_tx(sb + P3BAR + 8 * (22 + i), 8192);
                    tma_2d(sb + (i < 4 ? 12 + i : i - 4) * 8192, &tm_o1, i * 64, rowL, sb + P3BAR + 8 * (22 + i));
                }
            }
        }
        if (warp == 8) {
            if (redo) {
                if (lane == 0) { p3_load_w(0); p3_load_w(1); p3_load_w(2); p3_load_w(3); }
                __syncwarp();
                cnt_wait_warp(&g_cnt[0][qb * 32], cnt_target());
            }
            if (lane == 0) {
                asm volatile("fence.proxy.async.global;" ::: "memory");
                if (redo) { p3_load_o(0); p3_load_o(1); }
#pragma unroll 1
                for (int i = 0; i < 4; i++) {
                    mbar_expect_tx(sb + P3BAR + 8 * (6 + i), 8192);
                    tma_2d(sb + (16 + i) * 8192, &tm_o1, (12 + i) * 64, rowE, sb + P3BAR + 8 * (6 + i));
                }
#pragma unroll 1
                for (int i = 0; i < 8; i++) {
                    mbar_wait(sb + P3BAR + 8 * (30 + i), 0);
                    if (i < 4) {
                        mbar_expect_tx(sb + P3BAR + 8 * (10 + i), 8192);
                        tma_2d(sb + i * 8192, &tm_o1, (12 + i) * 64, rowL, sb + P3BAR + 8 * (10 + i));
                    }
                    mbar_expect_tx(sb + P3BAR + 8 * (14 + i), 8192);
                    tma_2d(sb + (i < 4 ? 8 + i : 12 + i) * 8192, &tm_o1, i * 64, rowE, sb + P3BAR + 8 * (14 + i));
                }
            }
        }
        return;
    }
    {
        float accA[32], accB[32];
#pragma unroll
        for (int i = 0; i < 32; i++) { accA[i] = 0.f; accB[i] = 0.f; }
        fence_regs(accA); fence_regs(accB);
        constexpr uint64_t da0 = make_desc(SMEM_BASE, 16, 1024, 1);
        constexpr uint64_t db0 = make_desc(SMEM_BASE, 8192, 1024, 1);
        const int row = (wg ? rowL : rowE) + w4 * 16;
        float g0 = 0.f, g1 = 0.f;
#pragma unroll
        for (int kb = 0; kb < 16; kb++) {
            const int j = kb & 7;
            const int wslot = kb < 4 ? kb : (kb < 12 ? 16 + kb : kb - 8);
            const int oslot = wg ? (j < 4 ? 12 + j : j - 4) : (j < 4 ? 8 + j : 12 + j);
            if ((kb & 3) == 0) mbar_wait_warp(sb + P3BAR + 8 * (kb >> 2), 0);
            if (kb >= 8) mbar_wait_warp(sb + P3BAR + 8 * (14 + j) + wg * 64, 0);
            else if (kb == 0) mbar_wait_warp(sb + P3BAR + 8 * (4 + wg), 0);
            else if (kb >= 4) mbar_wait_warp(sb + P3BAR + 8 * (2 + kb) + wg * 32, 0);
            if (kb == 0) {
                asm volatile("ld.relaxed.gpu.global.f32 %0, [%1];" : "=f"(g0) : "l"(g_gate + row + (lane >> 2)) : "memory");
                asm volatile("ld.relaxed.gpu.global.f32 %0, [%1];" : "=f"(g1) : "l"(g_gate + row + (lane >> 2) + 8) : "memory");
            }
            const uint64_t da = da0 + (uint64_t)(oslot * 512), db = db0 + (uint64_t)(wslot * 512);
            wg_fence();
#pragma unroll
            for (int k = 0; k < 4; k++) {
                if (kb < 8) wgmma_ss_n64_tb(accB, da + 2 * k, db + 128 * k);
                else wgmma_ss_n64_tb(accA, da + 2 * k, db + 128 * k);
            }
            wg_commit();
            if (kb == 7) wg_wait<0>(); else if (kb >= 1 && kb < 7) wg_wait<1>();
            if (kb >= 1 && kb < 8) {
                if (w4 == 0 && lane == 0) {
                    mbar_arrive(sb + P3BAR + 8 * (30 + kb - 1));
                    if (kb == 7) mbar_arrive(sb + P3BAR + 8 * 37);
                }
                __syncwarp();
            }
        }
        wg_wait<0>();
        fence_regs(accA); fence_regs(accB);
        const uint32_t toff = (8 + wg * 4) * 8192 + w4 * 2048;
        const int mrow = (lane & 7) + ((lane >> 3) & 1) * 8;
#pragma unroll
        for (int p = 0; p < 4; p++) {
            uint32_t r[4];
#pragma unroll
            for (int h = 0; h < 2; h++) {
                const int i = (2 * p + h) * 4;
                r[2 * h] = pack_bf16(g0 * accA[i] + (1.f - g0) * accB[i], g0 * accA[i + 1] + (1.f - g0) * accB[i + 1]);
                r[2 * h + 1] = pack_bf16(g1 * accA[i + 2] + (1.f - g1) * accB[i + 2], g1 * accA[i + 3] + (1.f - g1) * accB[i + 3]);
            }
            const int chunk = 2 * p + (lane >> 4);
            stmatrix_x4(sb + toff + mrow * 128 + ((chunk ^ (mrow & 7)) << 4), r[0], r[1], r[2], r[3]);
        }
        __syncwarp();
#pragma unroll
        for (int p = 0; p < 4; p++) {
            const int r = p * 4 + (lane >> 3), c = lane & 7;
            const uint4 v = *reinterpret_cast<const uint4*>(sp + toff + r * 128 + ((c ^ (r & 7)) << 4));
            *reinterpret_cast<uint4*>(out + (size_t)(row + r) * DM + n0 + c * 8) = v;
        }
    }
}

typedef CUresult (*EncodeFn)(CUtensorMap*, CUtensorMapDataType, cuuint32_t, void*, const cuuint64_t*, const cuuint64_t*,
                             const cuuint32_t*, const cuuint32_t*, CUtensorMapInterleave, CUtensorMapSwizzle,
                             CUtensorMapL2promotion, CUtensorMapFloatOOBfill);

void encode(EncodeFn fn, CUtensorMap* tm, const void* ptr, int rank, const cuuint64_t* dims, const cuuint64_t* strides,
            const cuuint32_t* box, CUtensorMapSwizzle swz) {
    const cuuint32_t es[4] = {1, 1, 1, 1};
    fn(tm, CU_TENSOR_MAP_DATA_TYPE_BFLOAT16, rank, const_cast<void*>(ptr), dims, strides, box, es, CU_TENSOR_MAP_INTERLEAVE_NONE,
       swz, CU_TENSOR_MAP_L2_PROMOTION_L2_256B, CU_TENSOR_MAP_FLOAT_OOB_FILL_NONE);
}

}

extern "C" void kernel_launch(void* const* d_in, const int* in_sizes, int n_in, void* d_out, int out_size) {
    (void)in_sizes; (void)n_in; (void)out_size;
    const __nv_bfloat16* x = (const __nv_bfloat16*)d_in[0];
    const __nv_bfloat16* gate_w = (const __nv_bfloat16*)d_in[6];
    static EncodeFn fn = nullptr;
    static void* ocat = nullptr;
    if (!fn) {
        cudaDriverEntryPointQueryResult qr;
        cudaGetDriverEntryPoint("cuTensorMapEncodeTiled", (void**)&fn, cudaEnableDefault, &qr);
        cudaGetSymbolAddress(&ocat, g_ocat);
        cudaFuncSetAttribute(fused_kernel, cudaFuncAttributeMaxDynamicSharedMemorySize, SMEM1_BYTES);
    }
    CUtensorMap tm_x, tm_wa, tm_wb, tm_woa4, tm_wob4, tm_o1, tm_o4;
    {
        const cuuint64_t dims[2] = {512, 2048}, str[1] = {1024};
        const cuuint32_t box[2] = {64, 256};
        encode(fn, &tm_x, x, 2, dims, str, box, CU_TENSOR_MAP_SWIZZLE_128B);
    }
    {
        const cuuint64_t dims[4] = {16, 512, 32, 3}, str[3] = {3072, 32, 1024};
        const cuuint32_t box[4] = {16, 64, 1, 3};
        encode(fn, &tm_wa, d_in[1], 4, dims, str, box, CU_TENSOR_MAP_SWIZZLE_32B);
        encode(fn, &tm_wb, d_in[4], 4, dims, str, box, CU_TENSOR_MAP_SWIZZLE_32B);
    }
    {
        const cuuint64_t dims[2] = {1024, 2048}, str[1] = {2048};
        const cuuint32_t box[2] = {64, 64};
        encode(fn, &tm_o1, ocat, 2, dims, str, box, CU_TENSOR_MAP_SWIZZLE_128B);
        const cuuint64_t dims3[3] = {64, 2048, 16}, str3[2] = {2048, 128};
        const cuuint32_t box3[3] = {64, 64, 4};
        encode(fn, &tm_o4, ocat, 3, dims3, str3, box3, CU_TENSOR_MAP_SWIZZLE_128B);
    }
    {
        const cuuint64_t dims[2] = {512, 512}, str[1] = {1024};
        const cuuint32_t box4[2] = {64, 256};
        encode(fn, &tm_woa4, d_in[2], 2, dims, str, box4, CU_TENSOR_MAP_SWIZZLE_128B);
        encode(fn, &tm_wob4, d_in[5], 2, dims, str, box4, CU_TENSOR_MAP_SWIZZLE_128B);
    }
    cudaLaunchAttribute at[1];
    at[0].id = cudaLaunchAttributeClusterDimension;
    at[0].val.clusterDim.x = 2; at[0].val.clusterDim.y = 1; at[0].val.clusterDim.z = 1;
    cudaLaunchConfig_t cfg = {};
    cfg.gridDim = dim3(128); cfg.blockDim = dim3(512); cfg.dynamicSmemBytes = SMEM1_BYTES;
    cfg.stream = cudaStreamPerThread; cfg.attrs = at; cfg.numAttrs = 1;
    cudaLaunchKernelEx(&cfg, fused_kernel, tm_x, tm_wa, tm_wb, tm_woa4, tm_wob4, tm_o1, tm_o4, x, gate_w, (__nv_bfloat16*)d_out);
}
```
